```python
import torch

def _softmax(x, axis=-1):
    return torch.softmax(x, dim=axis)

def _gelu(x):
    return torch.nn.functional.gelu(x, approximate='tanh')

def _silu(x):
    return torch.nn.functional.silu(x)

def _sigmoid(x):
    return torch.sigmoid(x)

def _layernorm(x, axis=-1, eps=1e-05):
    m = x.mean(dim=axis, keepdim=True)
    v = x.var(dim=axis, keepdim=True, unbiased=False)
    return (x - m) / torch.sqrt(v + eps)

def _scatter_add(tgt, idx, src, axis=0):
    return tgt.clone().index_add_(axis, idx, src)

def _segment_sum(src, seg, n):
    out = torch.zeros((n,) + src.shape[1:], dtype=src.dtype)
    return out.index_add_(0, seg, src)

def _pad(x, pw):
    flat = tuple((v for pair in reversed(pw) for v in pair))
    return torch.nn.functional.pad(x, flat)
kernel_name = 'adaLN_cond__linear_kernel_hedgehog__dense_activation_squared_relu__prompt'

def setup_inputs():

    _w = lambda a: (lambda t: t.to(torch.bfloat16) if t.is_floating_point() else t)(torch.as_tensor(a))

    def _A_setup():
        B, S, D, H = (1, 2048, 1024, 32)
        Dh = D // H
        return {'x': _w((lambda *s: torch.randn(*s, dtype=torch.bfloat16) * 0.05)(B, S, D)), 'wqkv': _w((lambda *s: torch.randn(*s, dtype=torch.bfloat16) * 0.4)(D, 3 * D)), 'w_phi': _w((lambda *s: torch.randn(*s, dtype=torch.bfloat16) * 0.4)(H, Dh, Dh) * Dh ** (-0.5)), 'wo': _w((lambda *s: torch.randn(*s, dtype=torch.bfloat16) * 0.05)(D, D))}
    _A_in = _A_setup()

    def _B_setup():
        B, S, D, F = (1, 2048, 1024, 3584)
        return {'x': _w((lambda *s: torch.randn(*s, dtype=torch.bfloat16) * 0.05)(B, S, D)), 'w1': _w((lambda *s: torch.randn(*s, dtype=torch.bfloat16) * 0.05)(D, F)), 'b1': _w((lambda *s: torch.randn(*s, dtype=torch.bfloat16) * 0.4)(F)), 'w2': _w((lambda *s: torch.randn(*s, dtype=torch.bfloat16) * 0.05)(F, D)), 'b2': _w((lambda *s: torch.randn(*s, dtype=torch.bfloat16) * 6.4)(D))}
    _B_in = _B_setup()
    return {'A_x': _A_in['x'], 'A_wqkv': _A_in['wqkv'], 'A_w_phi': _A_in['w_phi'], 'A_wo': _A_in['wo'], 'B_x': _B_in['x'], 'B_w1': _B_in['w1'], 'B_b1': _B_in['b1'], 'B_w2': _B_in['w2'], 'B_b2': _B_in['b2'], 'c': _w((lambda *s: torch.randn(*s, dtype=torch.bfloat16) * 0.1)(1, 1024) * 8.0), 'w_mod': _w((lambda *s: torch.randn(*s, dtype=torch.bfloat16) * 0.1)(1024, 6 * 1024) * 1024 ** (-0.5) * 8.0)}

def reference(A_x, A_wqkv, A_w_phi, A_wo, B_x, B_w1, B_b1, B_w2, B_b2, c, w_mod):

    def _A_ref(x, wqkv, w_phi, wo):
        B, S, D = x.shape
        H = 32
        Dh = D // H
        qkv = (lambda x, *d: x.permute(*d))((x @ wqkv).reshape(B, S, 3, H, Dh), 2, 0, 3, 1, 4)
        q, k, v = (qkv[0], qkv[1], qkv[2])
        pq = torch.einsum('bhsd,hdf->bhsf', q, w_phi)
        pk = torch.einsum('bhsd,hdf->bhsf', k, w_phi)
        phi_q = torch.concatenate([_softmax(pq, axis=-1), _softmax(-pq, axis=-1)], axis=-1)
        phi_k = torch.concatenate([_softmax(pk, axis=-1), _softmax(-pk, axis=-1)], axis=-1)
        kv = torch.einsum('bhsf,bhsd->bhfd', phi_k, v)
        z = torch.einsum('bhsf->bhf', phi_k)
        num = torch.einsum('bhqf,bhfd->bhqd', phi_q, kv)
        den = torch.einsum('bhqf,bhf->bhq', phi_q, z)[..., None] + 1e-06
        o = num / den
        return (lambda x, *d: x.permute(*d))(o, 0, 2, 1, 3).reshape(B, S, D) @ wo

    def _B_ref(x, w1, b1, w2, b2):
        h = torch.einsum('bsd,df->bsf', x, w1) + b1
        zero = torch.zeros_like(h)
        r = torch.where(h > zero, h, zero)
        h = r * r
        out = torch.einsum('bsf,fd->bsd', h, w2) + b2
        return out
    x = A_x
    mod = (_silu(c) @ w_mod).reshape(c.shape[0], 6, 1, -1)
    sa, ca, ga, sb, cb, gb = (mod[:, 0].clone(), mod[:, 1].clone(), mod[:, 2].clone(), mod[:, 3].clone(), mod[:, 4].clone(), mod[:, 5].clone())
    h = _layernorm(x, axis=-1) * (1 + ca) + sa
    x = x + ga * _A_ref(h, A_wqkv, A_w_phi, A_wo)
    h = _layernorm(x, axis=-1) * (1 + cb) + sb
    x = x + gb * _B_ref(h, B_w1, B_b1, B_w2, B_b2)
    return x
```

```cpp
#include <cuda_runtime.h>
#include <cuda_bf16.h>
#include <cuda.h>
#include <stdint.h>

typedef __nv_bfloat16 bf16;
#define SPIN_LIMIT (1u << 22)
constexpr int SEQ = 2048, DM = 1024, FF = 3584;

__device__ uint32_t g_epoch;
__device__ uint32_t g_done;
__device__ uint2 g_modpk[3072];
__device__ uint4 g_st1pk[SEQ];
__device__ uint4 g_utpk[FF];
__device__ __align__(1024) bf16 g_h[SEQ * DM];
__device__ __align__(1024) bf16 g_o[SEQ * DM];
__device__ __align__(1024) bf16 g_x1g[SEQ * DM];
__device__ __align__(1024) bf16 g_hid[SEQ * FF];
__device__ uint4 g_x1f[128 * 8 * 256];
__device__ float4 g_kvacc[2][32 * 5 * 128];
__device__ float2 g_st2[SEQ * 8];
__device__ __align__(128) uint32_t g_hflag[16 * 2 * 8];
__device__ __align__(128) uint32_t g_kvflag[8 * 32];
__device__ __align__(128) uint32_t g_oflag[16 * 2 * 8];
__device__ __align__(128) uint32_t g_xflag[16 * 2 * 8];
__device__ __align__(128) uint32_t g_hidflag[3 * 16 * 2 * 8];
#define TL(i) do { } while (0)

__device__ __forceinline__ uint32_t smem_u32(const void* p) { return (uint32_t)__cvta_generic_to_shared(p); }
__device__ __forceinline__ void mbar_init(uint32_t bar, uint32_t cnt) { asm volatile("mbarrier.init.shared::cta.b64 [%0], %1;" :: "r"(bar), "r"(cnt) : "memory"); }
__device__ __forceinline__ void mbar_expect_tx(uint32_t bar, uint32_t bytes) { asm volatile("mbarrier.arrive.expect_tx.shared::cta.b64 _, [%0], %1;" :: "r"(bar), "r"(bytes) : "memory"); }
__device__ __forceinline__ void mbar_arrive(uint32_t bar) { asm volatile("mbarrier.arrive.shared::cta.b64 _, [%0];" :: "r"(bar) : "memory"); }
__device__ __forceinline__ void mbar_arrive_cluster(uint32_t bar, uint32_t cta) {
  asm volatile("{\n.reg .b32 ra;\nmapa.shared::cluster.u32 ra, %0, %1;\nmbarrier.arrive.shared::cluster.b64 _, [ra];\n}\n" :: "r"(bar), "r"(cta) : "memory");
}
__device__ __forceinline__ bool mbar_try_wait(uint32_t bar, uint32_t parity) {
  uint32_t ok;
  asm volatile("{\n.reg .pred p;\nmbarrier.try_wait.parity.shared::cta.b64 p, [%1], %2;\nselp.u32 %0, 1, 0, p;\n}\n" : "=r"(ok) : "r"(bar), "r"(parity) : "memory");
  return ok;
}
__device__ __forceinline__ void spin_guard(uint32_t n) {
  asm volatile("{\n.reg .pred p;\n.reg .b32 a;\nmov.b32 a, 0x00fffffd;\nsetp.gt.u32 p, %0, %1;\n@p st.shared.u32 [a], %0;\n}\n" :: "r"(n), "n"(SPIN_LIMIT) : "memory");
}
__device__ __forceinline__ void mbar_wait(uint32_t bar, uint32_t parity) {
  uint32_t n = 0;
  while (!mbar_try_wait(bar, parity)) { spin_guard(++n); }
}
__device__ __forceinline__ void tma_load_2d(uint32_t dst, const CUtensorMap* tm, uint32_t bar, int c0, int c1) {
  asm volatile("cp.async.bulk.tensor.2d.shared::cluster.global.mbarrier::complete_tx::bytes [%0], [%1, {%3, %4}], [%2];"
    :: "r"(dst), "l"(tm), "r"(bar), "r"(c0), "r"(c1) : "memory");
}
__device__ __forceinline__ void tma_load_2d_mc(uint32_t dst, const CUtensorMap* tm, uint32_t bar, int c0, int c1, uint16_t mask) {
  asm volatile("cp.async.bulk.tensor.2d.shared::cluster.global.mbarrier::complete_tx::bytes.multicast::cluster [%0], [%1, {%3, %4}], [%2], %5;"
    :: "r"(dst), "l"(tm), "r"(bar), "r"(c0), "r"(c1), "h"(mask) : "memory");
}
__device__ __forceinline__ void tma_load_3d(uint32_t dst, const CUtensorMap* tm, uint32_t bar, int c0, int c1, int c2) {
  asm volatile("cp.async.bulk.tensor.3d.shared::cluster.global.mbarrier::complete_tx::bytes [%0], [%1, {%3, %4, %5}], [%2];"
    :: "r"(dst), "l"(tm), "r"(bar), "r"(c0), "r"(c1), "r"(c2) : "memory");
}
__device__ __forceinline__ void tma_store_2d(const CUtensorMap* tm, uint32_t src, int c0, int c1) {
  asm volatile("cp.async.bulk.tensor.2d.global.shared::cta.bulk_group [%0, {%2, %3}], [%1];" :: "l"(tm), "r"(src), "r"(c0), "r"(c1) : "memory");
}
__device__ __forceinline__ void bulk_commit() { asm volatile("cp.async.bulk.commit_group;" ::: "memory"); }
__device__ __forceinline__ void bulk_wait_read0() { asm volatile("cp.async.bulk.wait_group.read 0;" ::: "memory"); }
__device__ __forceinline__ void bulk_wait0() { asm volatile("cp.async.bulk.wait_group 0;" ::: "memory"); }
__device__ __forceinline__ void fence_async() { asm volatile("fence.proxy.async;" ::: "memory"); }
__device__ __forceinline__ void fence_async_smem() { asm volatile("fence.proxy.async.shared::cta;" ::: "memory"); }
__device__ __forceinline__ void prefetch_tmap(const CUtensorMap* tm) { asm volatile("prefetch.tensormap [%0];" :: "l"(tm) : "memory"); }
__device__ __forceinline__ void wgmma_fence() { asm volatile("wgmma.fence.sync.aligned;" ::: "memory"); }
__device__ __forceinline__ void wgmma_commit() { asm volatile("wgmma.commit_group.sync.aligned;" ::: "memory"); }
template<int N> __device__ __forceinline__ void wgmma_wait() { asm volatile("wgmma.wait_group.sync.aligned %0;" :: "n"(N) : "memory"); }
__device__ __forceinline__ uint64_t make_desc(uint32_t addr, uint32_t lbo, uint32_t sbo, uint32_t swz) {
  return (uint64_t)((addr & 0x3FFFF) >> 4) | ((uint64_t)(lbo >> 4) << 16) | ((uint64_t)(sbo >> 4) << 32) | ((uint64_t)swz << 62);
}
__device__ __forceinline__ void cluster_sync() {
  asm volatile("barrier.cluster.arrive.release.aligned;\nbarrier.cluster.wait.acquire.aligned;" ::: "memory");
}
__device__ __forceinline__ uint64_t gtimer() { uint64_t t; asm volatile("mov.u64 %0, %%globaltimer;" : "=l"(t)); return t; }
template<int R> __device__ __forceinline__ void reg_alloc() { asm volatile("setmaxnreg.inc.sync.aligned.u32 %0;" :: "n"(R)); }
template<int R> __device__ __forceinline__ void reg_dealloc() { asm volatile("setmaxnreg.dec.sync.aligned.u32 %0;" :: "n"(R)); }
__device__ __forceinline__ void bar_sync(int id, int n) { asm volatile("bar.sync %0, %1;" :: "r"(id), "r"(n) : "memory"); }
__device__ __forceinline__ uint32_t pack_bf16(float lo, float hi) { uint32_t r; asm("cvt.rn.bf16x2.f32 %0, %1, %2;" : "=r"(r) : "f"(hi), "f"(lo)); return r; }
__device__ __forceinline__ float bf_lo(uint32_t v) { return __uint_as_float(v << 16); }
__device__ __forceinline__ float bf_hi(uint32_t v) { return __uint_as_float(v & 0xffff0000u); }
__device__ __forceinline__ float bf_round(float v) { return bf_lo(pack_bf16(v, 0.f)); }
__device__ __forceinline__ void stmatrix_x4(uint32_t addr, uint32_t r0, uint32_t r1, uint32_t r2, uint32_t r3) {
  asm volatile("stmatrix.sync.aligned.m8n8.x4.shared.b16 [%0], {%1, %2, %3, %4};" :: "r"(addr), "r"(r0), "r"(r1), "r"(r2), "r"(r3) : "memory");
}
__device__ __forceinline__ void ldmatrix_x4(uint32_t addr, uint32_t& r0, uint32_t& r1, uint32_t& r2, uint32_t& r3) {
  asm volatile("ldmatrix.sync.aligned.m8n8.x4.shared.b16 {%0, %1, %2, %3}, [%4];" : "=r"(r0), "=r"(r1), "=r"(r2), "=r"(r3) : "r"(addr) : "memory");
}
__device__ __forceinline__ uint32_t ld_acquire(const uint32_t* p) { uint32_t v; asm volatile("ld.acquire.gpu.global.u32 %0, [%1];" : "=r"(v) : "l"(p) : "memory"); return v; }
__device__ __forceinline__ uint32_t ld_relaxed(const uint32_t* p) { uint32_t v; asm volatile("ld.relaxed.gpu.global.u32 %0, [%1];" : "=r"(v) : "l"(p) : "memory"); return v; }
__device__ __forceinline__ void st_release(uint32_t* p, uint32_t v) { asm volatile("st.release.gpu.global.u32 [%0], %1;" :: "l"(p), "r"(v) : "memory"); }
__device__ __forceinline__ uint4 ld_vol4(const void* p) { uint4 v; asm volatile("ld.volatile.global.v4.u32 {%0, %1, %2, %3}, [%4];" : "=r"(v.x), "=r"(v.y), "=r"(v.z), "=r"(v.w) : "l"(p) : "memory"); return v; }
__device__ __forceinline__ uint2 ld_vol2(const void* p) { uint2 v; asm volatile("ld.volatile.global.v2.u32 {%0, %1}, [%2];" : "=r"(v.x), "=r"(v.y) : "l"(p) : "memory"); return v; }
__device__ __forceinline__ void st_vol2(void* p, uint32_t a, uint32_t b) { asm volatile("st.volatile.global.v2.u32 [%0], {%1, %2};" :: "l"(p), "r"(a), "r"(b) : "memory"); }
__device__ __forceinline__ void st_vol4(void* p, uint32_t a, uint32_t b, uint32_t c, uint32_t d) { asm volatile("st.volatile.global.v4.u32 [%0], {%1, %2, %3, %4};" :: "l"(p), "r"(a), "r"(b), "r"(c), "r"(d) : "memory"); }
__device__ __forceinline__ uint4 ld_nc4(const void* p) { uint4 v; asm volatile("ld.global.nc.L1::no_allocate.v4.u32 {%0, %1, %2, %3}, [%4];" : "=r"(v.x), "=r"(v.y), "=r"(v.z), "=r"(v.w) : "l"(p)); return v; }
__device__ __forceinline__ uint32_t ld_nc1(const void* p) { uint32_t v; asm volatile("ld.global.nc.u32 %0, [%1];" : "=r"(v) : "l"(p)); return v; }
__device__ __forceinline__ void red_add4(float4* p, float a, float b, float c, float d) {
  asm volatile("red.global.add.v4.f32 [%0], {%1, %2, %3, %4};" :: "l"(p), "f"(a), "f"(b), "f"(c), "f"(d) : "memory");
}
__device__ __forceinline__ void sts4(uint32_t a, uint32_t x, uint32_t y, uint32_t z, uint32_t w) { asm volatile("st.shared.v4.u32 [%0], {%1, %2, %3, %4};" :: "r"(a), "r"(x), "r"(y), "r"(z), "r"(w) : "memory"); }
__device__ __forceinline__ void sts2(uint32_t a, uint32_t x, uint32_t y) { asm volatile("st.shared.v2.u32 [%0], {%1, %2};" :: "r"(a), "r"(x), "r"(y) : "memory"); }
__device__ __forceinline__ void sts1(uint32_t a, uint32_t x) { asm volatile("st.shared.u32 [%0], %1;" :: "r"(a), "r"(x) : "memory"); }
__device__ __forceinline__ uint4 lds4(uint32_t a) { uint4 v; asm volatile("ld.shared.v4.u32 {%0, %1, %2, %3}, [%4];" : "=r"(v.x), "=r"(v.y), "=r"(v.z), "=r"(v.w) : "r"(a) : "memory"); return v; }
__device__ __forceinline__ uint2 lds2(uint32_t a) { uint2 v; asm volatile("ld.shared.v2.u32 {%0, %1}, [%2];" : "=r"(v.x), "=r"(v.y) : "r"(a) : "memory"); return v; }
__device__ __forceinline__ uint32_t lds1(uint32_t a) { uint32_t v; asm volatile("ld.shared.u32 %0, [%1];" : "=r"(v) : "r"(a) : "memory"); return v; }
__device__ __forceinline__ float ex2(float x) { float y; asm("ex2.approx.ftz.f32 %0, %1;" : "=f"(y) : "f"(x)); return y; }
__device__ __forceinline__ float rcp(float x) { float y; asm("rcp.approx.ftz.f32 %0, %1;" : "=f"(y) : "f"(x)); return y; }
__device__ __forceinline__ void prefetch_l2(const void* p) { asm volatile("prefetch.global.L2 [%0];" :: "l"(p)); }

template<int TA, int TB> __device__ __forceinline__ void wgmma_ss_n256(float (&d)[128], uint64_t da, uint64_t db) {
  asm volatile("{\n.reg .pred p;\nsetp.ne.b32 p, 1, 0;\n"
    "wgmma.mma_async.sync.aligned.m64n256k16.f32.bf16.bf16 {%0, %1, %2, %3, %4, %5, %6, %7, %8, %9, %10, %11, %12, %13, %14, %15, %16, %17, %18, %19, %20, %21, %22, %23, %24, %25, %26, %27, %28, %29, %30, %31, %32, %33, %34, %35, %36, %37, %38, %39, %40, %41, %42, %43, %44, %45, %46, %47, %48, %49, %50, %51, %52, %53, %54, %55, %56, %57, %58, %59, %60, %61, %62, %63, %64, %65, %66, %67, %68, %69, %70, %71, %72, %73, %74, %75, %76, %77, %78, %79, %80, %81, %82, %83, %84, %85, %86, %87, %88, %89, %90, %91, %92, %93, %94, %95, %96, %97, %98, %99, %100, %101, %102, %103, %104, %105, %106, %107, %108, %109, %110, %111, %112, %113, %114, %115, %116, %117, %118, %119, %120, %121, %122, %123, %124, %125, %126, %127}, %128, %129, p, 1, 1, %130, %131;\n}\n"
    : "+f"(d[0]), "+f"(d[1]), "+f"(d[2]), "+f"(d[3]), "+f"(d[4]), "+f"(d[5]), "+f"(d[6]), "+f"(d[7]), "+f"(d[8]), "+f"(d[9]), "+f"(d[10]), "+f"(d[11]), "+f"(d[12]), "+f"(d[13]), "+f"(d[14]), "+f"(d[15]), "+f"(d[16]), "+f"(d[17]), "+f"(d[18]), "+f"(d[19]), "+f"(d[20]), "+f"(d[21]), "+f"(d[22]), "+f"(d[23]), "+f"(d[24]), "+f"(d[25]), "+f"(d[26]), "+f"(d[27]), "+f"(d[28]), "+f"(d[29]), "+f"(d[30]), "+f"(d[31]), "+f"(d[32]), "+f"(d[33]), "+f"(d[34]), "+f"(d[35]), "+f"(d[36]), "+f"(d[37]), "+f"(d[38]), "+f"(d[39]), "+f"(d[40]), "+f"(d[41]), "+f"(d[42]), "+f"(d[43]), "+f"(d[44]), "+f"(d[45]), "+f"(d[46]), "+f"(d[47]), "+f"(d[48]), "+f"(d[49]), "+f"(d[50]), "+f"(d[51]), "+f"(d[52]), "+f"(d[53]), "+f"(d[54]), "+f"(d[55]), "+f"(d[56]), "+f"(d[57]), "+f"(d[58]), "+f"(d[59]), "+f"(d[60]), "+f"(d[61]), "+f"(d[62]), "+f"(d[63]), "+f"(d[64]), "+f"(d[65]), "+f"(d[66]), "+f"(d[67]), "+f"(d[68]), "+f"(d[69]), "+f"(d[70]), "+f"(d[71]), "+f"(d[72]), "+f"(d[73]), "+f"(d[74]), "+f"(d[75]), "+f"(d[76]), "+f"(d[77]), "+f"(d[78]), "+f"(d[79]), "+f"(d[80]), "+f"(d[81]), "+f"(d[82]), "+f"(d[83]), "+f"(d[84]), "+f"(d[85]), "+f"(d[86]), "+f"(d[87]), "+f"(d[88]), "+f"(d[89]), "+f"(d[90]), "+f"(d[91]), "+f"(d[92]), "+f"(d[93]), "+f"(d[94]), "+f"(d[95]), "+f"(d[96]), "+f"(d[97]), "+f"(d[98]), "+f"(d[99]), "+f"(d[100]), "+f"(d[101]), "+f"(d[102]), "+f"(d[103]), "+f"(d[104]), "+f"(d[105]), "+f"(d[106]), "+f"(d[107]), "+f"(d[108]), "+f"(d[109]), "+f"(d[110]), "+f"(d[111]), "+f"(d[112]), "+f"(d[113]), "+f"(d[114]), "+f"(d[115]), "+f"(d[116]), "+f"(d[117]), "+f"(d[118]), "+f"(d[119]), "+f"(d[120]), "+f"(d[121]), "+f"(d[122]), "+f"(d[123]), "+f"(d[124]), "+f"(d[125]), "+f"(d[126]), "+f"(d[127])
    : "l"(da), "l"(db), "n"(TA), "n"(TB));
}
template<int TA, int TB> __device__ __forceinline__ void wgmma_ssz_n256(float (&d)[128], uint64_t da, uint64_t db) {
  asm volatile("{\n.reg .pred p;\nsetp.ne.b32 p, 0, 0;\n"
    "wgmma.mma_async.sync.aligned.m64n256k16.f32.bf16.bf16 {%0, %1, %2, %3, %4, %5, %6, %7, %8, %9, %10, %11, %12, %13, %14, %15, %16, %17, %18, %19, %20, %21, %22, %23, %24, %25, %26, %27, %28, %29, %30, %31, %32, %33, %34, %35, %36, %37, %38, %39, %40, %41, %42, %43, %44, %45, %46, %47, %48, %49, %50, %51, %52, %53, %54, %55, %56, %57, %58, %59, %60, %61, %62, %63, %64, %65, %66, %67, %68, %69, %70, %71, %72, %73, %74, %75, %76, %77, %78, %79, %80, %81, %82, %83, %84, %85, %86, %87, %88, %89, %90, %91, %92, %93, %94, %95, %96, %97, %98, %99, %100, %101, %102, %103, %104, %105, %106, %107, %108, %109, %110, %111, %112, %113, %114, %115, %116, %117, %118, %119, %120, %121, %122, %123, %124, %125, %126, %127}, %128, %129, p, 1, 1, %130, %131;\n}\n"
    : "=f"(d[0]), "=f"(d[1]), "=f"(d[2]), "=f"(d[3]), "=f"(d[4]), "=f"(d[5]), "=f"(d[6]), "=f"(d[7]), "=f"(d[8]), "=f"(d[9]), "=f"(d[10]), "=f"(d[11]), "=f"(d[12]), "=f"(d[13]), "=f"(d[14]), "=f"(d[15]), "=f"(d[16]), "=f"(d[17]), "=f"(d[18]), "=f"(d[19]), "=f"(d[20]), "=f"(d[21]), "=f"(d[22]), "=f"(d[23]), "=f"(d[24]), "=f"(d[25]), "=f"(d[26]), "=f"(d[27]), "=f"(d[28]), "=f"(d[29]), "=f"(d[30]), "=f"(d[31]), "=f"(d[32]), "=f"(d[33]), "=f"(d[34]), "=f"(d[35]), "=f"(d[36]), "=f"(d[37]), "=f"(d[38]), "=f"(d[39]), "=f"(d[40]), "=f"(d[41]), "=f"(d[42]), "=f"(d[43]), "=f"(d[44]), "=f"(d[45]), "=f"(d[46]), "=f"(d[47]), "=f"(d[48]), "=f"(d[49]), "=f"(d[50]), "=f"(d[51]), "=f"(d[52]), "=f"(d[53]), "=f"(d[54]), "=f"(d[55]), "=f"(d[56]), "=f"(d[57]), "=f"(d[58]), "=f"(d[59]), "=f"(d[60]), "=f"(d[61]), "=f"(d[62]), "=f"(d[63]), "=f"(d[64]), "=f"(d[65]), "=f"(d[66]), "=f"(d[67]), "=f"(d[68]), "=f"(d[69]), "=f"(d[70]), "=f"(d[71]), "=f"(d[72]), "=f"(d[73]), "=f"(d[74]), "=f"(d[75]), "=f"(d[76]), "=f"(d[77]), "=f"(d[78]), "=f"(d[79]), "=f"(d[80]), "=f"(d[81]), "=f"(d[82]), "=f"(d[83]), "=f"(d[84]), "=f"(d[85]), "=f"(d[86]), "=f"(d[87]), "=f"(d[88]), "=f"(d[89]), "=f"(d[90]), "=f"(d[91]), "=f"(d[92]), "=f"(d[93]), "=f"(d[94]), "=f"(d[95]), "=f"(d[96]), "=f"(d[97]), "=f"(d[98]), "=f"(d[99]), "=f"(d[100]), "=f"(d[101]), "=f"(d[102]), "=f"(d[103]), "=f"(d[104]), "=f"(d[105]), "=f"(d[106]), "=f"(d[107]), "=f"(d[108]), "=f"(d[109]), "=f"(d[110]), "=f"(d[111]), "=f"(d[112]), "=f"(d[113]), "=f"(d[114]), "=f"(d[115]), "=f"(d[116]), "=f"(d[117]), "=f"(d[118]), "=f"(d[119]), "=f"(d[120]), "=f"(d[121]), "=f"(d[122]), "=f"(d[123]), "=f"(d[124]), "=f"(d[125]), "=f"(d[126]), "=f"(d[127])
    : "l"(da), "l"(db), "n"(TA), "n"(TB));
}
template<int TA, int TB> __device__ __forceinline__ void wgmma_ss_n192(float (&d)[96], uint64_t da, uint64_t db) {
  asm volatile("{\n.reg .pred p;\nsetp.ne.b32 p, 1, 0;\n"
    "wgmma.mma_async.sync.aligned.m64n192k16.f32.bf16.bf16 {%0, %1, %2, %3, %4, %5, %6, %7, %8, %9, %10, %11, %12, %13, %14, %15, %16, %17, %18, %19, %20, %21, %22, %23, %24, %25, %26, %27, %28, %29, %30, %31, %32, %33, %34, %35, %36, %37, %38, %39, %40, %41, %42, %43, %44, %45, %46, %47, %48, %49, %50, %51, %52, %53, %54, %55, %56, %57, %58, %59, %60, %61, %62, %63, %64, %65, %66, %67, %68, %69, %70, %71, %72, %73, %74, %75, %76, %77, %78, %79, %80, %81, %82, %83, %84, %85, %86, %87, %88, %89, %90, %91, %92, %93, %94, %95}, %96, %97, p, 1, 1, %98, %99;\n}\n"
    : "+f"(d[0]), "+f"(d[1]), "+f"(d[2]), "+f"(d[3]), "+f"(d[4]), "+f"(d[5]), "+f"(d[6]), "+f"(d[7]), "+f"(d[8]), "+f"(d[9]), "+f"(d[10]), "+f"(d[11]), "+f"(d[12]), "+f"(d[13]), "+f"(d[14]), "+f"(d[15]), "+f"(d[16]), "+f"(d[17]), "+f"(d[18]), "+f"(d[19]), "+f"(d[20]), "+f"(d[21]), "+f"(d[22]), "+f"(d[23]), "+f"(d[24]), "+f"(d[25]), "+f"(d[26]), "+f"(d[27]), "+f"(d[28]), "+f"(d[29]), "+f"(d[30]), "+f"(d[31]), "+f"(d[32]), "+f"(d[33]), "+f"(d[34]), "+f"(d[35]), "+f"(d[36]), "+f"(d[37]), "+f"(d[38]), "+f"(d[39]), "+f"(d[40]), "+f"(d[41]), "+f"(d[42]), "+f"(d[43]), "+f"(d[44]), "+f"(d[45]), "+f"(d[46]), "+f"(d[47]), "+f"(d[48]), "+f"(d[49]), "+f"(d[50]), "+f"(d[51]), "+f"(d[52]), "+f"(d[53]), "+f"(d[54]), "+f"(d[55]), "+f"(d[56]), "+f"(d[57]), "+f"(d[58]), "+f"(d[59]), "+f"(d[60]), "+f"(d[61]), "+f"(d[62]), "+f"(d[63]), "+f"(d[64]), "+f"(d[65]), "+f"(d[66]), "+f"(d[67]), "+f"(d[68]), "+f"(d[69]), "+f"(d[70]), "+f"(d[71]), "+f"(d[72]), "+f"(d[73]), "+f"(d[74]), "+f"(d[75]), "+f"(d[76]), "+f"(d[77]), "+f"(d[78]), "+f"(d[79]), "+f"(d[80]), "+f"(d[81]), "+f"(d[82]), "+f"(d[83]), "+f"(d[84]), "+f"(d[85]), "+f"(d[86]), "+f"(d[87]), "+f"(d[88]), "+f"(d[89]), "+f"(d[90]), "+f"(d[91]), "+f"(d[92]), "+f"(d[93]), "+f"(d[94]), "+f"(d[95])
    : "l"(da), "l"(db), "n"(TA), "n"(TB));
}
template<int TA, int TB> __device__ __forceinline__ void wgmma_ssz_n192(float (&d)[96], uint64_t da, uint64_t db) {
  asm volatile("{\n.reg .pred p;\nsetp.ne.b32 p, 0, 0;\n"
    "wgmma.mma_async.sync.aligned.m64n192k16.f32.bf16.bf16 {%0, %1, %2, %3, %4, %5, %6, %7, %8, %9, %10, %11, %12, %13, %14, %15, %16, %17, %18, %19, %20, %21, %22, %23, %24, %25, %26, %27, %28, %29, %30, %31, %32, %33, %34, %35, %36, %37, %38, %39, %40, %41, %42, %43, %44, %45, %46, %47, %48, %49, %50, %51, %52, %53, %54, %55, %56, %57, %58, %59, %60, %61, %62, %63, %64, %65, %66, %67, %68, %69, %70, %71, %72, %73, %74, %75, %76, %77, %78, %79, %80, %81, %82, %83, %84, %85, %86, %87, %88, %89, %90, %91, %92, %93, %94, %95}, %96, %97, p, 1, 1, %98, %99;\n}\n"
    : "=f"(d[0]), "=f"(d[1]), "=f"(d[2]), "=f"(d[3]), "=f"(d[4]), "=f"(d[5]), "=f"(d[6]), "=f"(d[7]), "=f"(d[8]), "=f"(d[9]), "=f"(d[10]), "=f"(d[11]), "=f"(d[12]), "=f"(d[13]), "=f"(d[14]), "=f"(d[15]), "=f"(d[16]), "=f"(d[17]), "=f"(d[18]), "=f"(d[19]), "=f"(d[20]), "=f"(d[21]), "=f"(d[22]), "=f"(d[23]), "=f"(d[24]), "=f"(d[25]), "=f"(d[26]), "=f"(d[27]), "=f"(d[28]), "=f"(d[29]), "=f"(d[30]), "=f"(d[31]), "=f"(d[32]), "=f"(d[33]), "=f"(d[34]), "=f"(d[35]), "=f"(d[36]), "=f"(d[37]), "=f"(d[38]), "=f"(d[39]), "=f"(d[40]), "=f"(d[41]), "=f"(d[42]), "=f"(d[43]), "=f"(d[44]), "=f"(d[45]), "=f"(d[46]), "=f"(d[47]), "=f"(d[48]), "=f"(d[49]), "=f"(d[50]), "=f"(d[51]), "=f"(d[52]), "=f"(d[53]), "=f"(d[54]), "=f"(d[55]), "=f"(d[56]), "=f"(d[57]), "=f"(d[58]), "=f"(d[59]), "=f"(d[60]), "=f"(d[61]), "=f"(d[62]), "=f"(d[63]), "=f"(d[64]), "=f"(d[65]), "=f"(d[66]), "=f"(d[67]), "=f"(d[68]), "=f"(d[69]), "=f"(d[70]), "=f"(d[71]), "=f"(d[72]), "=f"(d[73]), "=f"(d[74]), "=f"(d[75]), "=f"(d[76]), "=f"(d[77]), "=f"(d[78]), "=f"(d[79]), "=f"(d[80]), "=f"(d[81]), "=f"(d[82]), "=f"(d[83]), "=f"(d[84]), "=f"(d[85]), "=f"(d[86]), "=f"(d[87]), "=f"(d[88]), "=f"(d[89]), "=f"(d[90]), "=f"(d[91]), "=f"(d[92]), "=f"(d[93]), "=f"(d[94]), "=f"(d[95])
    : "l"(da), "l"(db), "n"(TA), "n"(TB));
}
template<int TA, int TB> __device__ __forceinline__ void wgmma_ss_n128(float (&d)[64], uint64_t da, uint64_t db) {
  asm volatile("{\n.reg .pred p;\nsetp.ne.b32 p, 1, 0;\n"
    "wgmma.mma_async.sync.aligned.m64n128k16.f32.bf16.bf16 {%0, %1, %2, %3, %4, %5, %6, %7, %8, %9, %10, %11, %12, %13, %14, %15, %16, %17, %18, %19, %20, %21, %22, %23, %24, %25, %26, %27, %28, %29, %30, %31, %32, %33, %34, %35, %36, %37, %38, %39, %40, %41, %42, %43, %44, %45, %46, %47, %48, %49, %50, %51, %52, %53, %54, %55, %56, %57, %58, %59, %60, %61, %62, %63}, %64, %65, p, 1, 1, %66, %67;\n}\n"
    : "+f"(d[0]), "+f"(d[1]), "+f"(d[2]), "+f"(d[3]), "+f"(d[4]), "+f"(d[5]), "+f"(d[6]), "+f"(d[7]), "+f"(d[8]), "+f"(d[9]), "+f"(d[10]), "+f"(d[11]), "+f"(d[12]), "+f"(d[13]), "+f"(d[14]), "+f"(d[15]), "+f"(d[16]), "+f"(d[17]), "+f"(d[18]), "+f"(d[19]), "+f"(d[20]), "+f"(d[21]), "+f"(d[22]), "+f"(d[23]), "+f"(d[24]), "+f"(d[25]), "+f"(d[26]), "+f"(d[27]), "+f"(d[28]), "+f"(d[29]), "+f"(d[30]), "+f"(d[31]), "+f"(d[32]), "+f"(d[33]), "+f"(d[34]), "+f"(d[35]), "+f"(d[36]), "+f"(d[37]), "+f"(d[38]), "+f"(d[39]), "+f"(d[40]), "+f"(d[41]), "+f"(d[42]), "+f"(d[43]), "+f"(d[44]), "+f"(d[45]), "+f"(d[46]), "+f"(d[47]), "+f"(d[48]), "+f"(d[49]), "+f"(d[50]), "+f"(d[51]), "+f"(d[52]), "+f"(d[53]), "+f"(d[54]), "+f"(d[55]), "+f"(d[56]), "+f"(d[57]), "+f"(d[58]), "+f"(d[59]), "+f"(d[60]), "+f"(d[61]), "+f"(d[62]), "+f"(d[63])
    : "l"(da), "l"(db), "n"(TA), "n"(TB));
}
template<int TA, int TB> __device__ __forceinline__ void wgmma_ssz_n128(float (&d)[64], uint64_t da, uint64_t db) {
  asm volatile("{\n.reg .pred p;\nsetp.ne.b32 p, 0, 0;\n"
    "wgmma.mma_async.sync.aligned.m64n128k16.f32.bf16.bf16 {%0, %1, %2, %3, %4, %5, %6, %7, %8, %9, %10, %11, %12, %13, %14, %15, %16, %17, %18, %19, %20, %21, %22, %23, %24, %25, %26, %27, %28, %29, %30, %31, %32, %33, %34, %35, %36, %37, %38, %39, %40, %41, %42, %43, %44, %45, %46, %47, %48, %49, %50, %51, %52, %53, %54, %55, %56, %57, %58, %59, %60, %61, %62, %63}, %64, %65, p, 1, 1, %66, %67;\n}\n"
    : "=f"(d[0]), "=f"(d[1]), "=f"(d[2]), "=f"(d[3]), "=f"(d[4]), "=f"(d[5]), "=f"(d[6]), "=f"(d[7]), "=f"(d[8]), "=f"(d[9]), "=f"(d[10]), "=f"(d[11]), "=f"(d[12]), "=f"(d[13]), "=f"(d[14]), "=f"(d[15]), "=f"(d[16]), "=f"(d[17]), "=f"(d[18]), "=f"(d[19]), "=f"(d[20]), "=f"(d[21]), "=f"(d[22]), "=f"(d[23]), "=f"(d[24]), "=f"(d[25]), "=f"(d[26]), "=f"(d[27]), "=f"(d[28]), "=f"(d[29]), "=f"(d[30]), "=f"(d[31]), "=f"(d[32]), "=f"(d[33]), "=f"(d[34]), "=f"(d[35]), "=f"(d[36]), "=f"(d[37]), "=f"(d[38]), "=f"(d[39]), "=f"(d[40]), "=f"(d[41]), "=f"(d[42]), "=f"(d[43]), "=f"(d[44]), "=f"(d[45]), "=f"(d[46]), "=f"(d[47]), "=f"(d[48]), "=f"(d[49]), "=f"(d[50]), "=f"(d[51]), "=f"(d[52]), "=f"(d[53]), "=f"(d[54]), "=f"(d[55]), "=f"(d[56]), "=f"(d[57]), "=f"(d[58]), "=f"(d[59]), "=f"(d[60]), "=f"(d[61]), "=f"(d[62]), "=f"(d[63])
    : "l"(da), "l"(db), "n"(TA), "n"(TB));
}
template<int TA, int TB> __device__ __forceinline__ void wgmma_ss_n40(float (&d)[20], uint64_t da, uint64_t db) {
  asm volatile("{\n.reg .pred p;\nsetp.ne.b32 p, 1, 0;\n"
    "wgmma.mma_async.sync.aligned.m64n40k16.f32.bf16.bf16 {%0, %1, %2, %3, %4, %5, %6, %7, %8, %9, %10, %11, %12, %13, %14, %15, %16, %17, %18, %19}, %20, %21, p, 1, 1, %22, %23;\n}\n"
    : "+f"(d[0]), "+f"(d[1]), "+f"(d[2]), "+f"(d[3]), "+f"(d[4]), "+f"(d[5]), "+f"(d[6]), "+f"(d[7]), "+f"(d[8]), "+f"(d[9]), "+f"(d[10]), "+f"(d[11]), "+f"(d[12]), "+f"(d[13]), "+f"(d[14]), "+f"(d[15]), "+f"(d[16]), "+f"(d[17]), "+f"(d[18]), "+f"(d[19])
    : "l"(da), "l"(db), "n"(TA), "n"(TB));
}
template<int TA, int TB> __device__ __forceinline__ void wgmma_ssz_n40(float (&d)[20], uint64_t da, uint64_t db) {
  asm volatile("{\n.reg .pred p;\nsetp.ne.b32 p, 0, 0;\n"
    "wgmma.mma_async.sync.aligned.m64n40k16.f32.bf16.bf16 {%0, %1, %2, %3, %4, %5, %6, %7, %8, %9, %10, %11, %12, %13, %14, %15, %16, %17, %18, %19}, %20, %21, p, 1, 1, %22, %23;\n}\n"
    : "=f"(d[0]), "=f"(d[1]), "=f"(d[2]), "=f"(d[3]), "=f"(d[4]), "=f"(d[5]), "=f"(d[6]), "=f"(d[7]), "=f"(d[8]), "=f"(d[9]), "=f"(d[10]), "=f"(d[11]), "=f"(d[12]), "=f"(d[13]), "=f"(d[14]), "=f"(d[15]), "=f"(d[16]), "=f"(d[17]), "=f"(d[18]), "=f"(d[19])
    : "l"(da), "l"(db), "n"(TA), "n"(TB));
}
template<int TB> __device__ __forceinline__ void wgmma_rs_n256(float (&d)[128], uint32_t a0, uint32_t a1, uint32_t a2, uint32_t a3, uint64_t db) {
  asm volatile("{\n.reg .pred p;\nsetp.ne.b32 p, 1, 0;\n"
    "wgmma.mma_async.sync.aligned.m64n256k16.f32.bf16.bf16 {%0, %1, %2, %3, %4, %5, %6, %7, %8, %9, %10, %11, %12, %13, %14, %15, %16, %17, %18, %19, %20, %21, %22, %23, %24, %25, %26, %27, %28, %29, %30, %31, %32, %33, %34, %35, %36, %37, %38, %39, %40, %41, %42, %43, %44, %45, %46, %47, %48, %49, %50, %51, %52, %53, %54, %55, %56, %57, %58, %59, %60, %61, %62, %63, %64, %65, %66, %67, %68, %69, %70, %71, %72, %73, %74, %75, %76, %77, %78, %79, %80, %81, %82, %83, %84, %85, %86, %87, %88, %89, %90, %91, %92, %93, %94, %95, %96, %97, %98, %99, %100, %101, %102, %103, %104, %105, %106, %107, %108, %109, %110, %111, %112, %113, %114, %115, %116, %117, %118, %119, %120, %121, %122, %123, %124, %125, %126, %127}, {%128, %129, %130, %131}, %132, p, 1, 1, %133;\n}\n"
    : "+f"(d[0]), "+f"(d[1]), "+f"(d[2]), "+f"(d[3]), "+f"(d[4]), "+f"(d[5]), "+f"(d[6]), "+f"(d[7]), "+f"(d[8]), "+f"(d[9]), "+f"(d[10]), "+f"(d[11]), "+f"(d[12]), "+f"(d[13]), "+f"(d[14]), "+f"(d[15]), "+f"(d[16]), "+f"(d[17]), "+f"(d[18]), "+f"(d[19]), "+f"(d[20]), "+f"(d[21]), "+f"(d[22]), "+f"(d[23]), "+f"(d[24]), "+f"(d[25]), "+f"(d[26]), "+f"(d[27]), "+f"(d[28]), "+f"(d[29]), "+f"(d[30]), "+f"(d[31]), "+f"(d[32]), "+f"(d[33]), "+f"(d[34]), "+f"(d[35]), "+f"(d[36]), "+f"(d[37]), "+f"(d[38]), "+f"(d[39]), "+f"(d[40]), "+f"(d[41]), "+f"(d[42]), "+f"(d[43]), "+f"(d[44]), "+f"(d[45]), "+f"(d[46]), "+f"(d[47]), "+f"(d[48]), "+f"(d[49]), "+f"(d[50]), "+f"(d[51]), "+f"(d[52]), "+f"(d[53]), "+f"(d[54]), "+f"(d[55]), "+f"(d[56]), "+f"(d[57]), "+f"(d[58]), "+f"(d[59]), "+f"(d[60]), "+f"(d[61]), "+f"(d[62]), "+f"(d[63]), "+f"(d[64]), "+f"(d[65]), "+f"(d[66]), "+f"(d[67]), "+f"(d[68]), "+f"(d[69]), "+f"(d[70]), "+f"(d[71]), "+f"(d[72]), "+f"(d[73]), "+f"(d[74]), "+f"(d[75]), "+f"(d[76]), "+f"(d[77]), "+f"(d[78]), "+f"(d[79]), "+f"(d[80]), "+f"(d[81]), "+f"(d[82]), "+f"(d[83]), "+f"(d[84]), "+f"(d[85]), "+f"(d[86]), "+f"(d[87]), "+f"(d[88]), "+f"(d[89]), "+f"(d[90]), "+f"(d[91]), "+f"(d[92]), "+f"(d[93]), "+f"(d[94]), "+f"(d[95]), "+f"(d[96]), "+f"(d[97]), "+f"(d[98]), "+f"(d[99]), "+f"(d[100]), "+f"(d[101]), "+f"(d[102]), "+f"(d[103]), "+f"(d[104]), "+f"(d[105]), "+f"(d[106]), "+f"(d[107]), "+f"(d[108]), "+f"(d[109]), "+f"(d[110]), "+f"(d[111]), "+f"(d[112]), "+f"(d[113]), "+f"(d[114]), "+f"(d[115]), "+f"(d[116]), "+f"(d[117]), "+f"(d[118]), "+f"(d[119]), "+f"(d[120]), "+f"(d[121]), "+f"(d[122]), "+f"(d[123]), "+f"(d[124]), "+f"(d[125]), "+f"(d[126]), "+f"(d[127])
    : "r"(a0), "r"(a1), "r"(a2), "r"(a3), "l"(db), "n"(TB));
}
template<int TB> __device__ __forceinline__ void wgmma_rsz_n256(float (&d)[128], uint32_t a0, uint32_t a1, uint32_t a2, uint32_t a3, uint64_t db) {
  asm volatile("{\n.reg .pred p;\nsetp.ne.b32 p, 0, 0;\n"
    "wgmma.mma_async.sync.aligned.m64n256k16.f32.bf16.bf16 {%0, %1, %2, %3, %4, %5, %6, %7, %8, %9, %10, %11, %12, %13, %14, %15, %16, %17, %18, %19, %20, %21, %22, %23, %24, %25, %26, %27, %28, %29, %30, %31, %32, %33, %34, %35, %36, %37, %38, %39, %40, %41, %42, %43, %44, %45, %46, %47, %48, %49, %50, %51, %52, %53, %54, %55, %56, %57, %58, %59, %60, %61, %62, %63, %64, %65, %66, %67, %68, %69, %70, %71, %72, %73, %74, %75, %76, %77, %78, %79, %80, %81, %82, %83, %84, %85, %86, %87, %88, %89, %90, %91, %92, %93, %94, %95, %96, %97, %98, %99, %100, %101, %102, %103, %104, %105, %106, %107, %108, %109, %110, %111, %112, %113, %114, %115, %116, %117, %118, %119, %120, %121, %122, %123, %124, %125, %126, %127}, {%128, %129, %130, %131}, %132, p, 1, 1, %133;\n}\n"
    : "=f"(d[0]), "=f"(d[1]), "=f"(d[2]), "=f"(d[3]), "=f"(d[4]), "=f"(d[5]), "=f"(d[6]), "=f"(d[7]), "=f"(d[8]), "=f"(d[9]), "=f"(d[10]), "=f"(d[11]), "=f"(d[12]), "=f"(d[13]), "=f"(d[14]), "=f"(d[15]), "=f"(d[16]), "=f"(d[17]), "=f"(d[18]), "=f"(d[19]), "=f"(d[20]), "=f"(d[21]), "=f"(d[22]), "=f"(d[23]), "=f"(d[24]), "=f"(d[25]), "=f"(d[26]), "=f"(d[27]), "=f"(d[28]), "=f"(d[29]), "=f"(d[30]), "=f"(d[31]), "=f"(d[32]), "=f"(d[33]), "=f"(d[34]), "=f"(d[35]), "=f"(d[36]), "=f"(d[37]), "=f"(d[38]), "=f"(d[39]), "=f"(d[40]), "=f"(d[41]), "=f"(d[42]), "=f"(d[43]), "=f"(d[44]), "=f"(d[45]), "=f"(d[46]), "=f"(d[47]), "=f"(d[48]), "=f"(d[49]), "=f"(d[50]), "=f"(d[51]), "=f"(d[52]), "=f"(d[53]), "=f"(d[54]), "=f"(d[55]), "=f"(d[56]), "=f"(d[57]), "=f"(d[58]), "=f"(d[59]), "=f"(d[60]), "=f"(d[61]), "=f"(d[62]), "=f"(d[63]), "=f"(d[64]), "=f"(d[65]), "=f"(d[66]), "=f"(d[67]), "=f"(d[68]), "=f"(d[69]), "=f"(d[70]), "=f"(d[71]), "=f"(d[72]), "=f"(d[73]), "=f"(d[74]), "=f"(d[75]), "=f"(d[76]), "=f"(d[77]), "=f"(d[78]), "=f"(d[79]), "=f"(d[80]), "=f"(d[81]), "=f"(d[82]), "=f"(d[83]), "=f"(d[84]), "=f"(d[85]), "=f"(d[86]), "=f"(d[87]), "=f"(d[88]), "=f"(d[89]), "=f"(d[90]), "=f"(d[91]), "=f"(d[92]), "=f"(d[93]), "=f"(d[94]), "=f"(d[95]), "=f"(d[96]), "=f"(d[97]), "=f"(d[98]), "=f"(d[99]), "=f"(d[100]), "=f"(d[101]), "=f"(d[102]), "=f"(d[103]), "=f"(d[104]), "=f"(d[105]), "=f"(d[106]), "=f"(d[107]), "=f"(d[108]), "=f"(d[109]), "=f"(d[110]), "=f"(d[111]), "=f"(d[112]), "=f"(d[113]), "=f"(d[114]), "=f"(d[115]), "=f"(d[116]), "=f"(d[117]), "=f"(d[118]), "=f"(d[119]), "=f"(d[120]), "=f"(d[121]), "=f"(d[122]), "=f"(d[123]), "=f"(d[124]), "=f"(d[125]), "=f"(d[126]), "=f"(d[127])
    : "r"(a0), "r"(a1), "r"(a2), "r"(a3), "l"(db), "n"(TB));
}
template<int TB> __device__ __forceinline__ void wgmma_rs_n128(float (&d)[64], uint32_t a0, uint32_t a1, uint32_t a2, uint32_t a3, uint64_t db) {
  asm volatile("{\n.reg .pred p;\nsetp.ne.b32 p, 1, 0;\n"
    "wgmma.mma_async.sync.aligned.m64n128k16.f32.bf16.bf16 {%0, %1, %2, %3, %4, %5, %6, %7, %8, %9, %10, %11, %12, %13, %14, %15, %16, %17, %18, %19, %20, %21, %22, %23, %24, %25, %26, %27, %28, %29, %30, %31, %32, %33, %34, %35, %36, %37, %38, %39, %40, %41, %42, %43, %44, %45, %46, %47, %48, %49, %50, %51, %52, %53, %54, %55, %56, %57, %58, %59, %60, %61, %62, %63}, {%64, %65, %66, %67}, %68, p, 1, 1, %69;\n}\n"
    : "+f"(d[0]), "+f"(d[1]), "+f"(d[2]), "+f"(d[3]), "+f"(d[4]), "+f"(d[5]), "+f"(d[6]), "+f"(d[7]), "+f"(d[8]), "+f"(d[9]), "+f"(d[10]), "+f"(d[11]), "+f"(d[12]), "+f"(d[13]), "+f"(d[14]), "+f"(d[15]), "+f"(d[16]), "+f"(d[17]), "+f"(d[18]), "+f"(d[19]), "+f"(d[20]), "+f"(d[21]), "+f"(d[22]), "+f"(d[23]), "+f"(d[24]), "+f"(d[25]), "+f"(d[26]), "+f"(d[27]), "+f"(d[28]), "+f"(d[29]), "+f"(d[30]), "+f"(d[31]), "+f"(d[32]), "+f"(d[33]), "+f"(d[34]), "+f"(d[35]), "+f"(d[36]), "+f"(d[37]), "+f"(d[38]), "+f"(d[39]), "+f"(d[40]), "+f"(d[41]), "+f"(d[42]), "+f"(d[43]), "+f"(d[44]), "+f"(d[45]), "+f"(d[46]), "+f"(d[47]), "+f"(d[48]), "+f"(d[49]), "+f"(d[50]), "+f"(d[51]), "+f"(d[52]), "+f"(d[53]), "+f"(d[54]), "+f"(d[55]), "+f"(d[56]), "+f"(d[57]), "+f"(d[58]), "+f"(d[59]), "+f"(d[60]), "+f"(d[61]), "+f"(d[62]), "+f"(d[63])
    : "r"(a0), "r"(a1), "r"(a2), "r"(a3), "l"(db), "n"(TB));
}
template<int TB> __device__ __forceinline__ void wgmma_rsz_n128(float (&d)[64], uint32_t a0, uint32_t a1, uint32_t a2, uint32_t a3, uint64_t db) {
  asm volatile("{\n.reg .pred p;\nsetp.ne.b32 p, 0, 0;\n"
    "wgmma.mma_async.sync.aligned.m64n128k16.f32.bf16.bf16 {%0, %1, %2, %3, %4, %5, %6, %7, %8, %9, %10, %11, %12, %13, %14, %15, %16, %17, %18, %19, %20, %21, %22, %23, %24, %25, %26, %27, %28, %29, %30, %31, %32, %33, %34, %35, %36, %37, %38, %39, %40, %41, %42, %43, %44, %45, %46, %47, %48, %49, %50, %51, %52, %53, %54, %55, %56, %57, %58, %59, %60, %61, %62, %63}, {%64, %65, %66, %67}, %68, p, 1, 1, %69;\n}\n"
    : "=f"(d[0]), "=f"(d[1]), "=f"(d[2]), "=f"(d[3]), "=f"(d[4]), "=f"(d[5]), "=f"(d[6]), "=f"(d[7]), "=f"(d[8]), "=f"(d[9]), "=f"(d[10]), "=f"(d[11]), "=f"(d[12]), "=f"(d[13]), "=f"(d[14]), "=f"(d[15]), "=f"(d[16]), "=f"(d[17]), "=f"(d[18]), "=f"(d[19]), "=f"(d[20]), "=f"(d[21]), "=f"(d[22]), "=f"(d[23]), "=f"(d[24]), "=f"(d[25]), "=f"(d[26]), "=f"(d[27]), "=f"(d[28]), "=f"(d[29]), "=f"(d[30]), "=f"(d[31]), "=f"(d[32]), "=f"(d[33]), "=f"(d[34]), "=f"(d[35]), "=f"(d[36]), "=f"(d[37]), "=f"(d[38]), "=f"(d[39]), "=f"(d[40]), "=f"(d[41]), "=f"(d[42]), "=f"(d[43]), "=f"(d[44]), "=f"(d[45]), "=f"(d[46]), "=f"(d[47]), "=f"(d[48]), "=f"(d[49]), "=f"(d[50]), "=f"(d[51]), "=f"(d[52]), "=f"(d[53]), "=f"(d[54]), "=f"(d[55]), "=f"(d[56]), "=f"(d[57]), "=f"(d[58]), "=f"(d[59]), "=f"(d[60]), "=f"(d[61]), "=f"(d[62]), "=f"(d[63])
    : "r"(a0), "r"(a1), "r"(a2), "r"(a3), "l"(db), "n"(TB));
}
template<int TB> __device__ __forceinline__ void wgmma_rs_n40(float (&d)[20], uint32_t a0, uint32_t a1, uint32_t a2, uint32_t a3, uint64_t db) {
  asm volatile("{\n.reg .pred p;\nsetp.ne.b32 p, 1, 0;\n"
    "wgmma.mma_async.sync.aligned.m64n40k16.f32.bf16.bf16 {%0, %1, %2, %3, %4, %5, %6, %7, %8, %9, %10, %11, %12, %13, %14, %15, %16, %17, %18, %19}, {%20, %21, %22, %23}, %24, p, 1, 1, %25;\n}\n"
    : "+f"(d[0]), "+f"(d[1]), "+f"(d[2]), "+f"(d[3]), "+f"(d[4]), "+f"(d[5]), "+f"(d[6]), "+f"(d[7]), "+f"(d[8]), "+f"(d[9]), "+f"(d[10]), "+f"(d[11]), "+f"(d[12]), "+f"(d[13]), "+f"(d[14]), "+f"(d[15]), "+f"(d[16]), "+f"(d[17]), "+f"(d[18]), "+f"(d[19])
    : "r"(a0), "r"(a1), "r"(a2), "r"(a3), "l"(db), "n"(TB));
}
template<int TB> __device__ __forceinline__ void wgmma_rsz_n40(float (&d)[20], uint32_t a0, uint32_t a1, uint32_t a2, uint32_t a3, uint64_t db) {
  asm volatile("{\n.reg .pred p;\nsetp.ne.b32 p, 0, 0;\n"
    "wgmma.mma_async.sync.aligned.m64n40k16.f32.bf16.bf16 {%0, %1, %2, %3, %4, %5, %6, %7, %8, %9, %10, %11, %12, %13, %14, %15, %16, %17, %18, %19}, {%20, %21, %22, %23}, %24, p, 1, 1, %25;\n}\n"
    : "=f"(d[0]), "=f"(d[1]), "=f"(d[2]), "=f"(d[3]), "=f"(d[4]), "=f"(d[5]), "=f"(d[6]), "=f"(d[7]), "=f"(d[8]), "=f"(d[9]), "=f"(d[10]), "=f"(d[11]), "=f"(d[12]), "=f"(d[13]), "=f"(d[14]), "=f"(d[15]), "=f"(d[16]), "=f"(d[17]), "=f"(d[18]), "=f"(d[19])
    : "r"(a0), "r"(a1), "r"(a2), "r"(a3), "l"(db), "n"(TB));
}
template<int TB> __device__ __forceinline__ void wgmma_rs_n32(float (&d)[16], uint32_t a0, uint32_t a1, uint32_t a2, uint32_t a3, uint64_t db) {
  asm volatile("{\n.reg .pred p;\nsetp.ne.b32 p, 1, 0;\n"
    "wgmma.mma_async.sync.aligned.m64n32k16.f32.bf16.bf16 {%0, %1, %2, %3, %4, %5, %6, %7, %8, %9, %10, %11, %12, %13, %14, %15}, {%16, %17, %18, %19}, %20, p, 1, 1, %21;\n}\n"
    : "+f"(d[0]), "+f"(d[1]), "+f"(d[2]), "+f"(d[3]), "+f"(d[4]), "+f"(d[5]), "+f"(d[6]), "+f"(d[7]), "+f"(d[8]), "+f"(d[9]), "+f"(d[10]), "+f"(d[11]), "+f"(d[12]), "+f"(d[13]), "+f"(d[14]), "+f"(d[15])
    : "r"(a0), "r"(a1), "r"(a2), "r"(a3), "l"(db), "n"(TB));
}
template<int TB> __device__ __forceinline__ void wgmma_rsz_n32(float (&d)[16], uint32_t a0, uint32_t a1, uint32_t a2, uint32_t a3, uint64_t db) {
  asm volatile("{\n.reg .pred p;\nsetp.ne.b32 p, 0, 0;\n"
    "wgmma.mma_async.sync.aligned.m64n32k16.f32.bf16.bf16 {%0, %1, %2, %3, %4, %5, %6, %7, %8, %9, %10, %11, %12, %13, %14, %15}, {%16, %17, %18, %19}, %20, p, 1, 1, %21;\n}\n"
    : "=f"(d[0]), "=f"(d[1]), "=f"(d[2]), "=f"(d[3]), "=f"(d[4]), "=f"(d[5]), "=f"(d[6]), "=f"(d[7]), "=f"(d[8]), "=f"(d[9]), "=f"(d[10]), "=f"(d[11]), "=f"(d[12]), "=f"(d[13]), "=f"(d[14]), "=f"(d[15])
    : "r"(a0), "r"(a1), "r"(a2), "r"(a3), "l"(db), "n"(TB));
}

template<int N, bool Z> __device__ __forceinline__ void wgmma_ss(float (&d)[N / 2], uint64_t da, uint64_t db) {
  if constexpr (Z) {
    if constexpr (N == 256) wgmma_ssz_n256<0, 1>(d, da, db);
    else if constexpr (N == 192) wgmma_ssz_n192<0, 1>(d, da, db);
    else wgmma_ssz_n128<0, 1>(d, da, db);
  } else {
    if constexpr (N == 256) wgmma_ss_n256<0, 1>(d, da, db);
    else if constexpr (N == 192) wgmma_ss_n192<0, 1>(d, da, db);
    else wgmma_ss_n128<0, 1>(d, da, db);
  }
}
__device__ __forceinline__ void phi_mma(float (&d)[16], const uint32_t (&a)[8], uint32_t wphi) {
  wgmma_fence();
  wgmma_rsz_n32<1>(d, a[0], a[1], a[2], a[3], make_desc(wphi, 2048, 512, 2));
  wgmma_rs_n32<1>(d, a[4], a[5], a[6], a[7], make_desc(wphi + 1024, 2048, 512, 2));
  wgmma_commit();
}

constexpr int NJOBS = 7;
constexpr int NST = 16 * 6 + 56;
constexpr int J_KV = 0, J_Q = 16, J_WO = 32, J_F1A = 48, J_F1B = 64, J_F1C = 80, J_F2 = 96;
struct Sched { uint8_t off[NST]; int16_t need[NST]; };
constexpr Sched make_sched() {
  Sched s{};
  const int sz[NJOBS] = {6, 4, 4, 4, 4, 5, 4};
  const int lim[NJOBS] = {24, 20, 24, 24, 24, 24, 24};
  const int ns[NJOBS] = {16, 16, 16, 16, 16, 16, 56};
  int szs[NST] = {};
  int g = 0, off = 0;
  for (int j = 0; j < NJOBS; j++)
    for (int i = 0; i < ns[j]; i++) {
      if (off + sz[j] > lim[j]) off = 0;
      s.off[g] = (uint8_t)off; szs[g] = sz[j];
      int need = g - 8;
      for (int p = g - 1; p >= 0 && p > g - 8; p--)
        if (s.off[p] < off + sz[j] && off < s.off[p] + szs[p]) { need = p; break; }
      s.need[g] = (int16_t)need;
      off += sz[j]; g++;
    }
  return s;
}
__constant__ Sched c_sched = make_sched();

constexpr uint32_t SM_SCR = 160 * 1024;
constexpr uint32_t SM_MISC = 192 * 1024;
constexpr uint32_t SM_WPHI = SM_MISC;
constexpr uint32_t SM_STG = SM_MISC + 8192;
constexpr uint32_t SM_GS1 = SM_MISC + 24576;
constexpr uint32_t SM_GS2 = SM_MISC + 28672;
constexpr uint32_t SM_VEC = SM_MISC + 32768;
constexpr uint32_t SM_BAR = SM_MISC + 34816;
constexpr uint32_t SM_TOTAL = SM_MISC + 35840;
constexpr uint32_t B_FULL = SM_BAR, B_EMPTY = SM_BAR + 64, B_SCR = SM_BAR + 128, B_WPHI = SM_BAR + 136, B_VEC = SM_BAR + 144,
                   B_UT = SM_BAR + 152, B_GS1 = SM_BAR + 160;
constexpr uint32_t SM_RED = SM_BAR + 256;

struct Params {
  CUtensorMap tm_x, tm_h, tm_o, tm_x1g, tm_hid, tm_out, tm_wqkv, tm_wo, tm_w1a, tm_w1c, tm_w2, tm_wphi;
  const bf16 *x, *w1, *b1, *b2, *c, *wmod;
};

__device__ __forceinline__ float silu_bf(float v) { return bf_round(__fdividef(v, 1.f + __expf(-v))); }

struct Ctx { uint32_t sb; int wg, tid, lane, w4; uint32_t epoch; int m, n; };

__device__ __forceinline__ void release_stage(const Ctx& c, int g) {
  if (c.tid == 0) { uint32_t b = c.sb + B_EMPTY + 8 * (g & 7); mbar_arrive_cluster(b, 0); mbar_arrive_cluster(b, 1); }
}
template<int N, bool FIRST> __device__ __forceinline__ void mma_stage(const Ctx& c, float (&acc)[N / 2], int g) {
  mbar_wait(c.sb + B_FULL + 8 * (g & 7), (g >> 3) & 1);
  uint32_t st = c.sb + (uint32_t)c_sched.off[g] * 8192u;
  uint64_t da = make_desc(st + c.wg * 8192, 0, 1024, 1), db = make_desc(st + 16384, 8192, 1024, 1);
  wgmma_fence();
  wgmma_ss<N, FIRST>(acc, da, db);
#pragma unroll
  for (int k = 1; k < 4; k++) wgmma_ss<N, false>(acc, da + k * 2, db + k * 128);
  wgmma_commit();
}
template<int N> __device__ __forceinline__ void run_job(const Ctx& c, float (&acc)[N / 2], int g0, int ns) {
  mma_stage<N, true>(c, acc, g0);
  for (int i = 1; i < ns; i++) {
    mma_stage<N, false>(c, acc, g0 + i);
    wgmma_wait<1>();
    release_stage(c, g0 + i - 1);
  }
  wgmma_wait<0>();
  release_stage(c, g0 + ns - 1);
}

__device__ __forceinline__ void dual_softmax(const float (&p)[16], uint32_t (&ph)[16]) {
  constexpr float L2E = 1.4426950408889634f;
#pragma unroll
  for (int r = 0; r < 2; r++) {
    float mx = fmaxf(p[2 * r], p[2 * r + 1]), mn = fminf(p[2 * r], p[2 * r + 1]);
#pragma unroll
    for (int j = 1; j < 4; j++) { mx = fmaxf(mx, fmaxf(p[4 * j + 2 * r], p[4 * j + 2 * r + 1])); mn = fminf(mn, fminf(p[4 * j + 2 * r], p[4 * j + 2 * r + 1])); }
    mx = fmaxf(mx, __shfl_xor_sync(~0u, mx, 1)); mn = fminf(mn, __shfl_xor_sync(~0u, mn, 1));
    mx = fmaxf(mx, __shfl_xor_sync(~0u, mx, 2)); mn = fminf(mn, __shfl_xor_sync(~0u, mn, 2));
    float a = -mx * L2E, b = mn * L2E;
    float ep[8], en[8], sp = 0.f, sn = 0.f;
#pragma unroll
    for (int j = 0; j < 4; j++)
#pragma unroll
      for (int e = 0; e < 2; e++) {
        float v = p[4 * j + 2 * r + e];
        ep[2 * j + e] = ex2(fmaf(v, L2E, a)); en[2 * j + e] = ex2(fmaf(v, -L2E, b));
        sp += ep[2 * j + e]; sn += en[2 * j + e];
      }
    sp += __shfl_xor_sync(~0u, sp, 1); sn += __shfl_xor_sync(~0u, sn, 1);
    sp += __shfl_xor_sync(~0u, sp, 2); sn += __shfl_xor_sync(~0u, sn, 2);
    float ip = rcp(sp), in = rcp(sn);
#pragma unroll
    for (int j = 0; j < 4; j++) {
      ph[2 * j + r] = pack_bf16(ep[2 * j] * ip, ep[2 * j + 1] * ip);
      ph[8 + 2 * j + r] = pack_bf16(en[2 * j] * in, en[2 * j + 1] * in);
    }
  }
}

__device__ __forceinline__ uint32_t stm_addr(const Ctx& c, uint32_t tile, int cb) {
  int row = c.w4 * 16 + (c.lane & 15);
  return tile + row * 128 + (((cb + (c.lane >> 4)) ^ (row & 7)) << 4);
}

__device__ __forceinline__ void stg_acquire(const Ctx& c) {
  if (c.tid == 0) bulk_wait_read0();
  bar_sync(1 + c.wg, 128);
}
__device__ __forceinline__ void stg_store(const Ctx& c, const CUtensorMap* tm, int col) {
  fence_async_smem();
  bar_sync(1 + c.wg, 128);
  if (c.tid == 0) { tma_store_2d(tm, c.sb + SM_STG + c.wg * 8192, col, c.m * 128 + c.wg * 64); bulk_commit(); }
}
__device__ __forceinline__ void publish(const Ctx& c, uint32_t* flag) {
  if (c.tid == 0) { bulk_wait0(); fence_async(); __threadfence(); st_release(flag, c.epoch); }
}

template<int N> __device__ __forceinline__ void ffn1_epilogue(const Ctx& c, const Params& p, float (&acc)[N / 2], int ucol, int gcol, uint32_t* flag,
                                                              float mu0, float rs0, float mu1, float rs1) {
  int q = c.lane & 3;
#pragma unroll
  for (int pc = 0; pc < N / 64; pc++) {
    stg_acquire(c);
#pragma unroll
    for (int jj = 0; jj < 4; jj++) {
      uint32_t r[4];
#pragma unroll
      for (int e = 0; e < 2; e++) {
        int j = pc * 8 + jj * 2 + e;
        uint4 ut = lds4(c.sb + SM_WPHI + (ucol + j * 8 + q * 2) * 8);
        float u0 = __uint_as_float(ut.x), t0 = __uint_as_float(ut.y), u1 = __uint_as_float(ut.z), t1 = __uint_as_float(ut.w);
        float z0 = fmaxf(fmaf(rs0, fmaf(-mu0, u0, acc[4 * j]), t0), 0.f), z1 = fmaxf(fmaf(rs0, fmaf(-mu0, u1, acc[4 * j + 1]), t1), 0.f);
        float z2 = fmaxf(fmaf(rs1, fmaf(-mu1, u0, acc[4 * j + 2]), t0), 0.f), z3 = fmaxf(fmaf(rs1, fmaf(-mu1, u1, acc[4 * j + 3]), t1), 0.f);
        r[2 * e] = pack_bf16(z0 * z0, z1 * z1); r[2 * e + 1] = pack_bf16(z2 * z2, z3 * z3);
      }
      stmatrix_x4(stm_addr(c, c.sb + SM_STG + c.wg * 8192, jj * 2), r[0], r[1], r[2], r[3]);
    }
    stg_store(c, &p.tm_hid, gcol + pc * 64);
  }
  publish(c, flag);
}

__device__ __forceinline__ void gemv32(const bf16* w, int ld, uint32_t coef, uint32_t red, int ht, float& o0, float& o1) {
  int seg = ht & 3, r0 = ht >> 2;
  const bf16* wp = w + (size_t)r0 * ld + seg * 8;
  for (int i = ht; i < 1024; i += 64) prefetch_l2(w + (size_t)i * ld);
  float a[8], b[8];
#pragma unroll
  for (int e = 0; e < 8; e++) { a[e] = 0.f; b[e] = 0.f; }
  for (int it = 0; it < 16; it++) {
    uint4 v[4];
#pragma unroll
    for (int u = 0; u < 4; u++) v[u] = ld_nc4(wp + (size_t)(it * 64 + u * 16) * ld);
#pragma unroll
    for (int u = 0; u < 4; u++) {
      uint32_t cf = lds1(coef + (it * 64 + u * 16 + r0) * 4);
      float c0 = bf_lo(cf), c1 = bf_hi(cf);
      uint32_t vv[4] = {v[u].x, v[u].y, v[u].z, v[u].w};
#pragma unroll
      for (int e = 0; e < 4; e++) {
        float lo = bf_lo(vv[e]), hi = bf_hi(vv[e]);
        a[2 * e] = fmaf(c0, lo, a[2 * e]); a[2 * e + 1] = fmaf(c0, hi, a[2 * e + 1]);
        b[2 * e] = fmaf(c1, lo, b[2 * e]); b[2 * e + 1] = fmaf(c1, hi, b[2 * e + 1]);
      }
    }
  }
#pragma unroll
  for (int e = 0; e < 8; e++)
#pragma unroll
    for (int s = 4; s < 32; s <<= 1) { a[e] += __shfl_xor_sync(~0u, a[e], s); b[e] += __shfl_xor_sync(~0u, b[e], s); }
  bar_sync(4, 64);
  if ((ht & 31) < 4) {
#pragma unroll
    for (int e = 0; e < 8; e++) sts2(red + ((ht >> 5) * 32 + seg * 8 + e) * 8, __float_as_uint(a[e]), __float_as_uint(b[e]));
  }
  bar_sync(4, 64);
  uint2 x0 = lds2(red + (ht & 31) * 8), x1 = lds2(red + (32 + (ht & 31)) * 8);
  o0 = __uint_as_float(x0.x) + __uint_as_float(x1.x); o1 = __uint_as_float(x0.y) + __uint_as_float(x1.y);
}

__device__ __forceinline__ uint4 poll4(const void* p, uint32_t epoch) {
  uint4 v; uint32_t n = 0;
  while (true) { v = ld_vol4(p); if (v.y == epoch && v.w == epoch) break; spin_guard(++n); }
  return v;
}
__device__ __forceinline__ uint2 poll2(const void* p, uint32_t epoch) {
  uint2 v; uint32_t n = 0;
  while (true) { v = ld_vol2(p); if (v.y == epoch) break; spin_guard(++n); }
  return v;
}

__global__ void __cluster_dims__(2, 1, 1) __launch_bounds__(384, 1) mega_kernel(const __grid_constant__ Params p) {
  extern __shared__ __align__(1024) uint8_t smem_raw[];
  const uint32_t sb = smem_u32(smem_raw);
  const int tid = threadIdx.x, warp = tid >> 5, lane = tid & 31, wg = tid >> 7;
  const int b = blockIdx.x, m = b >> 3, n = b & 7, rank = b & 1;
  if (tid == 0) {
    TL(0);
    spin_guard((sb & 1023) ? ~0u : 0u);
    for (int s = 0; s < 8; s++) { mbar_init(sb + B_FULL + 8 * s, 1); mbar_init(sb + B_EMPTY + 8 * s, 4); }
    mbar_init(sb + B_SCR, 4); mbar_init(sb + B_WPHI, 1); mbar_init(sb + B_VEC, 64); mbar_init(sb + B_UT, 64); mbar_init(sb + B_GS1, 256);
    asm volatile("fence.mbarrier_init.release.cluster;" ::: "memory");
  }
  const uint32_t epoch = ld_relaxed(&g_epoch) + 1;
  __syncthreads();
  cluster_sync();

  if (wg == 2) {
    reg_dealloc<56>();
    if (warp == 8) {
      if (lane == 0) {
        mbar_expect_tx(sb + B_WPHI, 8192);
        tma_load_2d(sb + SM_WPHI, &p.tm_wphi, sb + B_WPHI, 0, n * 128);
        bool scr = false;
        for (int g = 0; g < NST; g++) {
          int need = c_sched.need[g];
          uint32_t off = c_sched.off[g];
          if (need >= 0) mbar_wait(sb + B_EMPTY + 8 * (need & 7), (need >> 3) & 1);
          if (g >= J_WO && !scr && off >= 17) { mbar_wait(sb + B_SCR, 0); scr = true; }
          uint32_t dst = sb + off * 8192u + 16384u, bar = sb + B_FULL + 8 * (g & 7);
          if (g < J_Q) {
            mbar_expect_tx(bar, 49152);
            tma_load_3d(dst, &p.tm_wqkv, bar, 0, g * 64, 16 + 2 * n);
            tma_load_3d(dst + 16384, &p.tm_wqkv, bar, 0, g * 64, 32 + 2 * n);
          } else if (g >= J_F1C && g < J_F2) {
            mbar_expect_tx(bar, 40960);
            tma_load_3d(dst, &p.tm_w1c, bar, 0, (g - J_F1C) * 64, 32 + 3 * n);
          } else {
            mbar_expect_tx(bar, 32768);
            const CUtensorMap* tm = g < J_WO ? &p.tm_wqkv : g < J_F1A ? &p.tm_wo : g < J_F1C ? &p.tm_w1a : &p.tm_w2;
            int k = g < J_F2 ? (g & 15) : g - J_F2;
            int ch = (g >= J_F1B && g < J_F1C) ? 16 + 2 * n : 2 * n;
            tma_load_3d(dst, tm, bar, 0, k * 64, ch);
          }
        }
      }
    } else if (warp == 9) {
      bool scr = false;
      uint32_t mask = 0;
      const uint32_t* flags = g_hflag + (m * 2 + rank) * 8;
      for (int g = 0; g < NST; g++) {
        int need = c_sched.need[g];
        uint32_t off = c_sched.off[g];
        int k = g < J_F2 ? (g & 15) : g - J_F2;
        uint32_t want;
        if (g < J_WO) want = 0xF;
        else if (g < J_F2) want = 1u << (k >> 1);
        else want = 1u << (k < 32 ? ((k & 15) >> 1) : (k - 32) / 3);
        if (g == J_WO) { flags = g_oflag + (m * 2 + rank) * 8; mask = 0; }
        if (g == J_F1A) { flags = g_xflag + (m * 2 + rank) * 8; mask = 0; }
        if (g == J_F2 || g == J_F2 + 16 || g == J_F2 + 32) { flags = g_hidflag + (((g - J_F2) >> 4) * 32 + m * 2 + rank) * 8; mask = 0; }
        if ((mask & want) != want) {
          uint32_t it = 0;
          do {
            uint32_t v = lane < 8 ? ld_acquire(flags + lane) : 0u;
            mask = __ballot_sync(~0u, lane < 8 && v == epoch);
            spin_guard(++it);
          } while ((mask & want) != want);
          fence_async();
        }
        if (lane == 0) {
          if (need >= 0) mbar_wait(sb + B_EMPTY + 8 * (need & 7), (need >> 3) & 1);
          if (g >= J_WO && !scr && off >= 17) { mbar_wait(sb + B_SCR, 0); scr = true; }
          const CUtensorMap* tm = g < J_WO ? &p.tm_h : g < J_F1A ? &p.tm_o : g < J_F2 ? &p.tm_x1g : &p.tm_hid;
          tma_load_2d_mc(sb + off * 8192u + rank * 8192u, tm, sb + B_FULL + 8 * (g & 7), k * 64, m * 128 + rank * 64, 3);
        }
        __syncwarp();
      }
    } else {
      const int ht = tid - 320;
      for (int i = ht; i < 160; i += 64) g_kvacc[(epoch + 1) & 1][b * 160 + i] = make_float4(0.f, 0.f, 0.f, 0.f);
      for (int i = ht; i < 512; i += 64) {
        uint32_t cv = ld_nc1(p.c + 2 * i);
        sts2(sb + SM_GS2 + i * 8, pack_bf16(silu_bf(bf_lo(cv)), 0.f), pack_bf16(silu_bf(bf_hi(cv)), 0.f));
      }
      mbar_wait(sb + B_GS1, 0);
      bar_sync(4, 64);
      float o0, o1;
      gemv32(p.wmod + 2048 + b * 32, 6144, sb + SM_GS2, sb + SM_RED, ht, o0, o1);
      {
        float nb = __shfl_down_sync(~0u, o0, 1);
        if (ht < 32 && !(ht & 1)) st_vol2(&g_modpk[1024 + b * 16 + (ht >> 1)], pack_bf16(o0, nb), epoch);
      }
      if (ht == 0) TL(48);
      bar_sync(4, 64);
      for (int i = ht; i < 256; i += 64) {
        uint4 s = poll4(&g_modpk[1536 + 2 * i], epoch), cc = poll4(&g_modpk[2048 + 2 * i], epoch);
        sts4(sb + SM_GS2 + i * 16, pack_bf16(1.f + bf_lo(cc.x), bf_lo(s.x)), pack_bf16(1.f + bf_hi(cc.x), bf_hi(s.x)),
             pack_bf16(1.f + bf_lo(cc.z), bf_lo(s.z)), pack_bf16(1.f + bf_hi(cc.z), bf_hi(s.z)));
      }
      {
        uint2 ga = poll2(&g_modpk[1024 + n * 64 + ht], epoch), cb = poll2(&g_modpk[2048 + n * 64 + ht], epoch), gb = poll2(&g_modpk[2560 + n * 64 + ht], epoch);
        uint32_t b2 = ld_nc1(p.b2 + n * 128 + 2 * ht);
        sts4(sb + SM_VEC + ht * 16, __float_as_uint(bf_lo(ga.x)), __float_as_uint(bf_round(1.f + bf_lo(cb.x))), __float_as_uint(bf_hi(ga.x)), __float_as_uint(bf_round(1.f + bf_hi(cb.x))));
        sts4(sb + SM_VEC + 1024 + ht * 16, __float_as_uint(bf_lo(gb.x)), __float_as_uint(bf_lo(b2)), __float_as_uint(bf_hi(gb.x)), __float_as_uint(bf_hi(b2)));
      }
      mbar_arrive(sb + B_VEC);
      if (ht == 0) TL(49);
      bar_sync(4, 64);
      if (b < 112) {
        gemv32(p.w1 + b * 32, FF, sb + SM_GS2, sb + SM_RED, ht, o0, o1);
        if (ht < 32) st_vol4(&g_utpk[b * 32 + ht], __float_as_uint(o0), epoch, __float_as_uint(o1 + __bfloat162float(p.b1[b * 32 + ht])), epoch);
      }
      if (ht == 0) TL(50);
      mbar_wait(sb + B_SCR, 0);
      for (int i = ht; i < 448; i += 64) {
        int col = i < 128 ? n * 128 + i : i < 256 ? 1024 + n * 128 + (i - 128) : 2048 + n * 192 + (i - 256);
        uint4 v = poll4(&g_utpk[col], epoch);
        sts2(sb + SM_WPHI + i * 8, v.x, v.z);
      }
      mbar_arrive(sb + B_UT);
      if (ht == 0) TL(51);
    }
    __syncwarp();
    cluster_sync();
  } else {
    reg_alloc<224>();
    Ctx c; c.sb = sb; c.wg = wg; c.tid = tid & 127; c.lane = lane; c.w4 = warp & 3; c.epoch = epoch; c.m = m; c.n = n;
    const int q = lane & 3;
    {
      uint4 wv[8], xv[2][4];
      const bf16* wp = p.wmod + (size_t)(tid >> 1) * 6144 + b * 16 + (tid & 1) * 8;
#pragma unroll
      for (int i = 0; i < 8; i++) wv[i] = ld_nc4(wp + (size_t)i * 128 * 6144);
      const int row0 = m * 128 + n * 16 + warp * 2;
#pragma unroll
      for (int r = 0; r < 2; r++)
#pragma unroll
        for (int i = 0; i < 4; i++) xv[r][i] = ld_nc4(p.x + (size_t)(row0 + r) * DM + i * 256 + lane * 8);
      float a[8];
#pragma unroll
      for (int e = 0; e < 8; e++) a[e] = 0.f;
#pragma unroll
      for (int i = 0; i < 8; i++) {
        float cf = silu_bf(__bfloat162float(p.c[(tid >> 1) + i * 128]));
        uint32_t vv[4] = {wv[i].x, wv[i].y, wv[i].z, wv[i].w};
#pragma unroll
        for (int e = 0; e < 4; e++) { a[2 * e] = fmaf(cf, bf_lo(vv[e]), a[2 * e]); a[2 * e + 1] = fmaf(cf, bf_hi(vv[e]), a[2 * e + 1]); }
      }
#pragma unroll
      for (int e = 0; e < 8; e++)
#pragma unroll
        for (int s = 2; s < 32; s <<= 1) a[e] += __shfl_xor_sync(~0u, a[e], s);
      if (lane < 2) {
        sts4(sb + SM_STG + warp * 64 + lane * 32, __float_as_uint(a[0]), __float_as_uint(a[1]), __float_as_uint(a[2]), __float_as_uint(a[3]));
        sts4(sb + SM_STG + warp * 64 + lane * 32 + 16, __float_as_uint(a[4]), __float_as_uint(a[5]), __float_as_uint(a[6]), __float_as_uint(a[7]));
      }
      bar_sync(3, 256);
      if (tid < 8) {
        float s0 = 0.f, s1 = 0.f;
#pragma unroll
        for (int w = 0; w < 8; w++) { uint2 v = lds2(sb + SM_STG + w * 64 + tid * 8); s0 += __uint_as_float(v.x); s1 += __uint_as_float(v.y); }
        st_vol2(&g_modpk[b * 8 + tid], pack_bf16(s0, s1), epoch);
      }
      if (tid == 0) TL(1);
      float mu[2], rs[2];
#pragma unroll
      for (int r = 0; r < 2; r++) {
        float s = 0.f;
#pragma unroll
        for (int i = 0; i < 4; i++) { uint32_t vv[4] = {xv[r][i].x, xv[r][i].y, xv[r][i].z, xv[r][i].w};
#pragma unroll
          for (int e = 0; e < 4; e++) s += bf_lo(vv[e]) + bf_hi(vv[e]); }
#pragma unroll
        for (int o = 1; o < 32; o <<= 1) s += __shfl_xor_sync(~0u, s, o);
        float mean = s * (1.f / DM), v2 = 0.f;
#pragma unroll
        for (int i = 0; i < 4; i++) { uint32_t vv[4] = {xv[r][i].x, xv[r][i].y, xv[r][i].z, xv[r][i].w};
#pragma unroll
          for (int e = 0; e < 4; e++) { float d0 = bf_lo(vv[e]) - mean, d1 = bf_hi(vv[e]) - mean; v2 = fmaf(d0, d0, v2); v2 = fmaf(d1, d1, v2); } }
#pragma unroll
        for (int o = 1; o < 32; o <<= 1) v2 += __shfl_xor_sync(~0u, v2, o);
        mu[r] = mean; rs[r] = rsqrtf(v2 * (1.f / DM) + 1e-5f);
      }
      {
        uint4 s = poll4(&g_modpk[2 * tid], epoch), cc = poll4(&g_modpk[512 + 2 * tid], epoch);
        sts4(sb + SM_GS1 + tid * 16, pack_bf16(1.f + bf_lo(cc.x), bf_lo(s.x)), pack_bf16(1.f + bf_hi(cc.x), bf_hi(s.x)),
             pack_bf16(1.f + bf_lo(cc.z), bf_lo(s.z)), pack_bf16(1.f + bf_hi(cc.z), bf_hi(s.z)));
      }
      mbar_arrive(sb + B_GS1);
      bar_sync(3, 256);
      if (tid == 0) TL(2);
#pragma unroll
      for (int i = 0; i < 4; i++) {
        uint4 g0 = lds4(sb + SM_GS1 + (i * 256 + lane * 8) * 4), g1 = lds4(sb + SM_GS1 + (i * 256 + lane * 8) * 4 + 16);
        uint32_t gg[8] = {g0.x, g0.y, g0.z, g0.w, g1.x, g1.y, g1.z, g1.w};
#pragma unroll
        for (int r = 0; r < 2; r++) {
          uint32_t vv[4] = {xv[r][i].x, xv[r][i].y, xv[r][i].z, xv[r][i].w}, o[4];
#pragma unroll
          for (int e = 0; e < 4; e++)
            o[e] = pack_bf16(fmaf((bf_lo(vv[e]) - mu[r]) * rs[r], bf_lo(gg[2 * e]), bf_hi(gg[2 * e])),
                             fmaf((bf_hi(vv[e]) - mu[r]) * rs[r], bf_lo(gg[2 * e + 1]), bf_hi(gg[2 * e + 1])));
          *(uint4*)(g_h + (size_t)(row0 + r) * DM + i * 256 + lane * 8) = make_uint4(o[0], o[1], o[2], o[3]);
        }
      }
      bar_sync(3, 256);
      if (tid == 0) { __threadfence(); st_release(&g_hflag[(m * 2 + (n >> 2)) * 8 + (n & 3)], epoch); TL(3); }
    }
    {
      float acc[128];
      run_job<256>(c, acc, J_KV, 16);
      if (tid == 0) TL(4);
      bar_sync(3, 256);
      mbar_wait(sb + B_WPHI, 0);
      const uint32_t phi_t = sb + SM_SCR + wg * 16384, v_t = phi_t + 8192;
      {
        int row = c.tid >> 1;
        if (!(c.tid & 1)) sts4(v_t + row * 128 + ((4 ^ (row & 7)) << 4), 0x3f803f80u, 0x3f803f80u, 0x3f803f80u, 0x3f803f80u);
      }
#pragma unroll
      for (int hh = 0; hh < 4; hh++) {
        float pk[16];
        uint32_t af[8];
#pragma unroll
        for (int i = 0; i < 8; i++) af[i] = pack_bf16(acc[hh * 16 + 2 * i], acc[hh * 16 + 2 * i + 1]);
        phi_mma(pk, af, sb + SM_WPHI + hh * 2048);
        wgmma_wait<0>();
        uint32_t ph[16];
        dual_softmax(pk, ph);
        if (hh > 0) bar_sync(1 + wg, 128);
#pragma unroll
        for (int jj = 0; jj < 4; jj++) stmatrix_x4(stm_addr(c, phi_t, jj * 2), ph[4 * jj], ph[4 * jj + 1], ph[4 * jj + 2], ph[4 * jj + 3]);
#pragma unroll
        for (int jj = 0; jj < 2; jj++) {
          int j0 = 16 + hh * 4 + 2 * jj;
          stmatrix_x4(stm_addr(c, v_t, jj * 2), pack_bf16(acc[4 * j0], acc[4 * j0 + 1]), pack_bf16(acc[4 * j0 + 2], acc[4 * j0 + 3]),
                      pack_bf16(acc[4 * j0 + 4], acc[4 * j0 + 5]), pack_bf16(acc[4 * j0 + 6], acc[4 * j0 + 7]));
        }
        fence_async_smem();
        bar_sync(1 + wg, 128);
        float kv[20];
        wgmma_fence();
        wgmma_ssz_n40<1, 1>(kv, make_desc(phi_t, 8192, 1024, 1), make_desc(v_t, 8192, 1024, 1));
#pragma unroll
        for (int s = 1; s < 4; s++)
          wgmma_ss_n40<1, 1>(kv, make_desc(phi_t + s * 2048, 8192, 1024, 1), make_desc(v_t + s * 2048, 8192, 1024, 1));
        wgmma_commit();
        wgmma_wait<0>();
        float4* dst = &g_kvacc[epoch & 1][(n * 4 + hh) * 640 + c.tid];
#pragma unroll
        for (int j = 0; j < 5; j++) red_add4(dst + j * 128, kv[4 * j], kv[4 * j + 1], kv[4 * j + 2], kv[4 * j + 3]);
      }
      bar_sync(1 + wg, 128);
      if (c.tid == 0) { __threadfence(); st_release(&g_kvflag[n * 32 + m * 2 + wg], epoch); }
      if (tid == 0) TL(5);
    }
    {
      float acc[64];
      run_job<128>(c, acc, J_Q, 16);
      if (tid == 0) TL(6);
      {
        uint32_t it = 0;
        while (!__all_sync(~0u, ld_acquire(&g_kvflag[n * 32 + lane]) == epoch)) { spin_guard(++it); }
      }
      if (tid == 0) TL(7);
      bar_sync(3, 256);
      {
        const float4* src = &g_kvacc[epoch & 1][(n * 4 + wg * 2) * 640 + c.tid];
        uint4 v[10];
#pragma unroll
        for (int i = 0; i < 10; i++) v[i] = ld_vol4(src + i * 128);
        int f = c.w4 * 16 + (lane >> 2);
#pragma unroll
        for (int i = 0; i < 10; i++) {
          uint32_t a = sb + SM_SCR + (wg * 2 + i / 5) * 8192 + f * 128 + (((i % 5) ^ (f & 7)) << 4) + q * 4;
          sts1(a, pack_bf16(__uint_as_float(v[i].x), __uint_as_float(v[i].y)));
          sts1(a + 1024, pack_bf16(__uint_as_float(v[i].z), __uint_as_float(v[i].w)));
        }
        fence_async_smem();
      }
      bar_sync(3, 256);
#pragma unroll
      for (int hh = 0; hh < 4; hh++) {
        float pq[16];
        uint32_t af[8];
#pragma unroll
        for (int i = 0; i < 8; i++) af[i] = pack_bf16(acc[hh * 16 + 2 * i], acc[hh * 16 + 2 * i + 1]);
        phi_mma(pq, af, sb + SM_WPHI + hh * 2048);
        wgmma_wait<0>();
        uint32_t ph[16];
        dual_softmax(pq, ph);
        float nd[20];
        wgmma_fence();
        wgmma_rsz_n40<1>(nd, ph[0], ph[1], ph[2], ph[3], make_desc(sb + SM_SCR + hh * 8192, 8192, 1024, 1));
#pragma unroll
        for (int s = 1; s < 4; s++)
          wgmma_rs_n40<1>(nd, ph[4 * s], ph[4 * s + 1], ph[4 * s + 2], ph[4 * s + 3], make_desc(sb + SM_SCR + hh * 8192 + s * 2048, 8192, 1024, 1));
        wgmma_commit();
        wgmma_wait<0>();
        float i0 = rcp(nd[16] + 1e-6f), i1 = rcp(nd[18] + 1e-6f);
        if (!(hh & 1)) stg_acquire(c);
#pragma unroll
        for (int jj = 0; jj < 2; jj++)
          stmatrix_x4(stm_addr(c, sb + SM_STG + wg * 8192, (hh & 1) * 4 + jj * 2), pack_bf16(nd[8 * jj] * i0, nd[8 * jj + 1] * i0), pack_bf16(nd[8 * jj + 2] * i1, nd[8 * jj + 3] * i1),
                      pack_bf16(nd[8 * jj + 4] * i0, nd[8 * jj + 5] * i0), pack_bf16(nd[8 * jj + 6] * i1, nd[8 * jj + 7] * i1));
        if (hh & 1) stg_store(c, &p.tm_o, n * 128 + (hh >> 1) * 64);
      }
      if (c.tid == 0) { mbar_arrive_cluster(sb + B_SCR, 0); mbar_arrive_cluster(sb + B_SCR, 1); }
      publish(c, &g_oflag[(m * 2 + wg) * 8 + n]);
      if (tid == 0) TL(8);
    }
    const int r0 = m * 128 + wg * 64 + c.w4 * 16 + (lane >> 2);
    {
      float acc[64];
      uint32_t xr[32];
#pragma unroll
      for (int j = 0; j < 16; j++) {
        xr[2 * j] = ld_nc1(p.x + (size_t)r0 * DM + n * 128 + j * 8 + q * 2);
        xr[2 * j + 1] = ld_nc1(p.x + (size_t)(r0 + 8) * DM + n * 128 + j * 8 + q * 2);
      }
      run_job<128>(c, acc, J_WO, 16);
      if (tid == 0) TL(9);
      mbar_wait(sb + B_VEC, 0);
      float s0 = 0.f, s1 = 0.f;
#pragma unroll
      for (int pc = 0; pc < 2; pc++) {
        stg_acquire(c);
#pragma unroll
        for (int jj = 0; jj < 4; jj++) {
          uint32_t r[4];
#pragma unroll
          for (int e = 0; e < 2; e++) {
            int j = pc * 8 + jj * 2 + e;
            uint4 gv = lds4(sb + SM_VEC + (j * 4 + q) * 16);
            float ga0 = __uint_as_float(gv.x), g20 = __uint_as_float(gv.y), ga1 = __uint_as_float(gv.z), g21 = __uint_as_float(gv.w);
            uint32_t a = pack_bf16(fmaf(ga0, acc[4 * j], bf_lo(xr[2 * j])), fmaf(ga1, acc[4 * j + 1], bf_hi(xr[2 * j])));
            uint32_t bb = pack_bf16(fmaf(ga0, acc[4 * j + 2], bf_lo(xr[2 * j + 1])), fmaf(ga1, acc[4 * j + 3], bf_hi(xr[2 * j + 1])));
            xr[2 * j] = a; xr[2 * j + 1] = bb;
            s0 += bf_lo(a) + bf_hi(a); s1 += bf_lo(bb) + bf_hi(bb);
            r[2 * e] = pack_bf16(bf_lo(a) * g20, bf_hi(a) * g21); r[2 * e + 1] = pack_bf16(bf_lo(bb) * g20, bf_hi(bb) * g21);
          }
          stmatrix_x4(stm_addr(c, sb + SM_STG + wg * 8192, jj * 2), r[0], r[1], r[2], r[3]);
        }
        if (pc == 1) {
          s0 += __shfl_xor_sync(~0u, s0, 1); s1 += __shfl_xor_sync(~0u, s1, 1);
          s0 += __shfl_xor_sync(~0u, s0, 2); s1 += __shfl_xor_sync(~0u, s1, 2);
          s0 *= (1.f / 128); s1 *= (1.f / 128);
          float v0 = 0.f, v1 = 0.f;
#pragma unroll
          for (int j = 0; j < 16; j++) {
            float d0 = bf_lo(xr[2 * j]) - s0, d1 = bf_hi(xr[2 * j]) - s0, d2 = bf_lo(xr[2 * j + 1]) - s1, d3 = bf_hi(xr[2 * j + 1]) - s1;
            v0 = fmaf(d0, d0, v0); v0 = fmaf(d1, d1, v0); v1 = fmaf(d2, d2, v1); v1 = fmaf(d3, d3, v1);
          }
          v0 += __shfl_xor_sync(~0u, v0, 1); v1 += __shfl_xor_sync(~0u, v1, 1);
          v0 += __shfl_xor_sync(~0u, v0, 2); v1 += __shfl_xor_sync(~0u, v1, 2);
          if (q == 0) { g_st2[r0 * 8 + n] = make_float2(s0, v0); g_st2[(r0 + 8) * 8 + n] = make_float2(s1, v1); }
        }
        stg_store(c, &p.tm_x1g, n * 128 + pc * 64);
      }
      publish(c, &g_xflag[(m * 2 + wg) * 8 + n]);
#pragma unroll
      for (int i = 0; i < 8; i++) g_x1f[(b * 8 + i) * 256 + tid] = make_uint4(xr[4 * i], xr[4 * i + 1], xr[4 * i + 2], xr[4 * i + 3]);
      if (tid == 0) TL(10);
    }
    float mu0, rs0, mu1, rs1;
    {
      float acc[64];
      run_job<128>(c, acc, J_F1A, 16);
      if (tid == 0) TL(11);
      {
        uint4 a = ld_vol4(&g_st2[r0 * 8 + q * 2]), bb = ld_vol4(&g_st2[(r0 + 8) * 8 + q * 2]);
        float m0 = __uint_as_float(a.x) + __uint_as_float(a.z), m1 = __uint_as_float(bb.x) + __uint_as_float(bb.z);
        m0 += __shfl_xor_sync(~0u, m0, 1); m1 += __shfl_xor_sync(~0u, m1, 1);
        m0 += __shfl_xor_sync(~0u, m0, 2); m1 += __shfl_xor_sync(~0u, m1, 2);
        m0 *= 0.125f; m1 *= 0.125f;
        float d0 = __uint_as_float(a.x) - m0, d1 = __uint_as_float(a.z) - m0, d2 = __uint_as_float(bb.x) - m1, d3 = __uint_as_float(bb.z) - m1;
        float v0 = __uint_as_float(a.y) + __uint_as_float(a.w) + 128.f * (d0 * d0 + d1 * d1);
        float v1 = __uint_as_float(bb.y) + __uint_as_float(bb.w) + 128.f * (d2 * d2 + d3 * d3);
        v0 += __shfl_xor_sync(~0u, v0, 1); v1 += __shfl_xor_sync(~0u, v1, 1);
        v0 += __shfl_xor_sync(~0u, v0, 2); v1 += __shfl_xor_sync(~0u, v1, 2);
        mu0 = m0; mu1 = m1; rs0 = rsqrtf(v0 * (1.f / DM) + 1e-5f); rs1 = rsqrtf(v1 * (1.f / DM) + 1e-5f);
      }
      mbar_wait(sb + B_UT, 0);
      ffn1_epilogue<128>(c, p, acc, 0, n * 128, &g_hidflag[(m * 2 + wg) * 8 + n], mu0, rs0, mu1, rs1);
      if (tid == 0) TL(12);
      run_job<128>(c, acc, J_F1B, 16);
      if (tid == 0) TL(13);
      ffn1_epilogue<128>(c, p, acc, 128, 1024 + n * 128, &g_hidflag[(32 + m * 2 + wg) * 8 + n], mu0, rs0, mu1, rs1);
      if (tid == 0) TL(14);
    }
    {
      float acc[96];
      run_job<192>(c, acc, J_F1C, 16);
      if (tid == 0) TL(15);
      ffn1_epilogue<192>(c, p, acc, 256, 2048 + n * 192, &g_hidflag[(64 + m * 2 + wg) * 8 + n], mu0, rs0, mu1, rs1);
      if (tid == 0) TL(16);
    }
    {
      float acc[64];
      uint32_t xr[32];
#pragma unroll
      for (int i = 0; i < 8; i++) { uint4 v = g_x1f[(b * 8 + i) * 256 + tid]; xr[4 * i] = v.x; xr[4 * i + 1] = v.y; xr[4 * i + 2] = v.z; xr[4 * i + 3] = v.w; }
      run_job<128>(c, acc, J_F2, 56);
      if (tid == 0) TL(17);
#pragma unroll
      for (int pc = 0; pc < 2; pc++) {
        stg_acquire(c);
#pragma unroll
        for (int jj = 0; jj < 4; jj++) {
          uint32_t r[4];
#pragma unroll
          for (int e = 0; e < 2; e++) {
            int j = pc * 8 + jj * 2 + e;
            uint4 gv = lds4(sb + SM_VEC + 1024 + (j * 4 + q) * 16);
            float gb0 = __uint_as_float(gv.x), b20 = __uint_as_float(gv.y), gb1 = __uint_as_float(gv.z), b21 = __uint_as_float(gv.w);
            r[2 * e] = pack_bf16(fmaf(gb0, acc[4 * j] + b20, bf_lo(xr[2 * j])), fmaf(gb1, acc[4 * j + 1] + b21, bf_hi(xr[2 * j])));
            r[2 * e + 1] = pack_bf16(fmaf(gb0, acc[4 * j + 2] + b20, bf_lo(xr[2 * j + 1])), fmaf(gb1, acc[4 * j + 3] + b21, bf_hi(xr[2 * j + 1])));
          }
          stmatrix_x4(stm_addr(c, sb + SM_STG + wg * 8192, jj * 2), r[0], r[1], r[2], r[3]);
        }
        stg_store(c, &p.tm_out, n * 128 + pc * 64);
      }
      if (c.tid == 0) bulk_wait0();
      if (tid == 0) TL(18);
    }
    __syncwarp();
    cluster_sync();
    if (tid == 0) {
      uint32_t t = atomicInc(&g_done, 127);
      if (t == 127) g_epoch = epoch;
    }
  }
}

typedef CUresult (*PFN_encodeTiled)(CUtensorMap*, CUtensorMapDataType, cuuint32_t, void*, const cuuint64_t*, const cuuint64_t*, const cuuint32_t*,
                                    const cuuint32_t*, CUtensorMapInterleave, CUtensorMapSwizzle, CUtensorMapL2promotion, CUtensorMapFloatOOBfill);
static void map_2d(PFN_encodeTiled enc, CUtensorMap* m, const void* ptr, uint64_t rows, uint64_t cols, uint32_t brows, uint32_t bcols, CUtensorMapSwizzle sw) {
  cuuint64_t dims[2] = {cols, rows}; cuuint64_t strides[1] = {cols * 2}; cuuint32_t box[2] = {bcols, brows}; cuuint32_t es[2] = {1, 1};
  enc(m, CU_TENSOR_MAP_DATA_TYPE_BFLOAT16, 2, (void*)ptr, dims, strides, box, es, CU_TENSOR_MAP_INTERLEAVE_NONE, sw,
      CU_TENSOR_MAP_L2_PROMOTION_L2_256B, CU_TENSOR_MAP_FLOAT_OOB_FILL_NONE);
}
static void map_3d(PFN_encodeTiled enc, CUtensorMap* m, const void* ptr, uint64_t rows, uint64_t cols, uint32_t nchunks) {
  cuuint64_t dims[3] = {64, rows, cols / 64}; cuuint64_t strides[2] = {cols * 2, 128}; cuuint32_t box[3] = {64, 64, nchunks}; cuuint32_t es[3] = {1, 1, 1};
  enc(m, CU_TENSOR_MAP_DATA_TYPE_BFLOAT16, 3, (void*)ptr, dims, strides, box, es, CU_TENSOR_MAP_INTERLEAVE_NONE, CU_TENSOR_MAP_SWIZZLE_128B,
      CU_TENSOR_MAP_L2_PROMOTION_L2_256B, CU_TENSOR_MAP_FLOAT_OOB_FILL_NONE);
}

extern "C" void kernel_launch(void* const* d_in, const int* in_sizes, int n_in, void* d_out, int out_size) {
  void* fp = nullptr; cudaDriverEntryPointQueryResult qr;
  cudaGetDriverEntryPoint("cuTensorMapEncodeTiled", &fp, cudaEnableDefault, &qr);
  PFN_encodeTiled enc = (PFN_encodeTiled)fp;
  void *ph, *po, *px1g, *phid;
  cudaGetSymbolAddress(&ph, g_h); cudaGetSymbolAddress(&po, g_o); cudaGetSymbolAddress(&px1g, g_x1g); cudaGetSymbolAddress(&phid, g_hid);
  Params p;
  map_2d(enc, &p.tm_x, d_in[0], SEQ, DM, 64, 64, CU_TENSOR_MAP_SWIZZLE_128B);
  map_2d(enc, &p.tm_h, ph, SEQ, DM, 64, 64, CU_TENSOR_MAP_SWIZZLE_128B);
  map_2d(enc, &p.tm_o, po, SEQ, DM, 64, 64, CU_TENSOR_MAP_SWIZZLE_128B);
  map_2d(enc, &p.tm_x1g, px1g, SEQ, DM, 64, 64, CU_TENSOR_MAP_SWIZZLE_128B);
  map_2d(enc, &p.tm_hid, phid, SEQ, FF, 64, 64, CU_TENSOR_MAP_SWIZZLE_128B);
  map_2d(enc, &p.tm_out, d_out, SEQ, DM, 64, 64, CU_TENSOR_MAP_SWIZZLE_128B);
  map_3d(enc, &p.tm_wqkv, d_in[1], DM, 3 * DM, 2);
  map_3d(enc, &p.tm_wo, d_in[3], DM, DM, 2);
  map_3d(enc, &p.tm_w1a, d_in[5], DM, FF, 2);
  map_3d(enc, &p.tm_w1c, d_in[5], DM, FF, 3);
  map_3d(enc, &p.tm_w2, d_in[7], FF, DM, 2);
  map_2d(enc, &p.tm_wphi, d_in[2], 1024, 32, 128, 32, CU_TENSOR_MAP_SWIZZLE_64B);
  p.x = (const bf16*)d_in[0]; p.w1 = (const bf16*)d_in[5]; p.b1 = (const bf16*)d_in[6]; p.b2 = (const bf16*)d_in[8];
  p.c = (const bf16*)d_in[9]; p.wmod = (const bf16*)d_in[10];
  cudaFuncSetAttribute(mega_kernel, cudaFuncAttributeMaxDynamicSharedMemorySize, SM_TOTAL);
  mega_kernel<<<128, 384, SM_TOTAL>>>(p);
}
```

```cpp
#include <cuda_runtime.h>
#include <cuda_bf16.h>
#include <cuda.h>
#include <stdint.h>
#include <type_traits>

typedef __nv_bfloat16 bf16;
#define SPIN_LIMIT (1u << 22)
constexpr int SEQ = 2048, DM = 1024, FF = 3584;

__device__ uint32_t g_epoch;
__device__ uint32_t g_done;
__device__ uint2 g_modpk[3072];
__device__ uint4 g_st1pk[SEQ];
__device__ uint4 g_st2pk[SEQ * 8];
__device__ uint4 g_utpk[FF];
__device__ __align__(1024) uint8_t g_h[SEQ * DM * 2];
__device__ __align__(1024) uint8_t g_o[SEQ * DM * 2];
__device__ __align__(1024) uint8_t g_x1g[SEQ * DM * 2];
__device__ __align__(1024) uint8_t g_hid[SEQ * FF * 2];
__device__ uint4 g_x1f[128 * 8 * 256];
__device__ float4 g_kvacc[2][32 * 5 * 128];
__device__ __align__(128) uint32_t g_hflag[16 * 2 * 32];
__device__ __align__(128) uint32_t g_kvflag[8 * 32];
__device__ __align__(128) uint32_t g_oflag[16 * 32];
__device__ __align__(128) uint32_t g_xflag[16 * 32];
__device__ __align__(128) uint32_t g_hidflag[3 * 16 * 2 * 32];
#define TL(i) do { } while (0)

__device__ __forceinline__ uint32_t smem_u32(const void* p) { return (uint32_t)__cvta_generic_to_shared(p); }
__device__ __forceinline__ void mbar_init(uint32_t bar, uint32_t cnt) { asm volatile("mbarrier.init.shared::cta.b64 [%0], %1;" :: "r"(bar), "r"(cnt) : "memory"); }
__device__ __forceinline__ void mbar_expect_tx(uint32_t bar, uint32_t bytes) { asm volatile("mbarrier.arrive.expect_tx.shared::cta.b64 _, [%0], %1;" :: "r"(bar), "r"(bytes) : "memory"); }
__device__ __forceinline__ void mbar_arrive(uint32_t bar) { asm volatile("mbarrier.arrive.shared::cta.b64 _, [%0];" :: "r"(bar) : "memory"); }
__device__ __forceinline__ void mbar_arrive_cluster(uint32_t bar, uint32_t cta) {
  asm volatile("{\n.reg .b32 ra;\nmapa.shared::cluster.u32 ra, %0, %1;\nmbarrier.arrive.shared::cluster.b64 _, [ra];\n}\n" :: "r"(bar), "r"(cta) : "memory");
}
__device__ __forceinline__ bool mbar_try_wait(uint32_t bar, uint32_t parity) {
  uint32_t ok;
  asm volatile("{\n.reg .pred p;\nmbarrier.try_wait.parity.shared::cta.b64 p, [%1], %2;\nselp.u32 %0, 1, 0, p;\n}\n" : "=r"(ok) : "r"(bar), "r"(parity) : "memory");
  return ok;
}
__device__ __forceinline__ void spin_guard(uint32_t n) {
  asm volatile("{\n.reg .pred p;\n.reg .b32 a;\nmov.b32 a, 0x00fffffd;\nsetp.gt.u32 p, %0, %1;\n@p st.shared.u32 [a], %0;\n}\n" :: "r"(n), "n"(SPIN_LIMIT) : "memory");
}
__device__ __forceinline__ void mbar_wait(uint32_t bar, uint32_t parity) {
  uint32_t n = 0;
  while (!mbar_try_wait(bar, parity)) { spin_guard(++n); }
}
__device__ __forceinline__ void tma_load_2d(uint32_t dst, const CUtensorMap* tm, uint32_t bar, int c0, int c1) {
  asm volatile("cp.async.bulk.tensor.2d.shared::cluster.global.mbarrier::complete_tx::bytes [%0], [%1, {%3, %4}], [%2];"
    :: "r"(dst), "l"(tm), "r"(bar), "r"(c0), "r"(c1) : "memory");
}
__device__ __forceinline__ void tma_load_2d_mc(uint32_t dst, const CUtensorMap* tm, uint32_t bar, int c0, int c1, uint16_t mask) {
  asm volatile("cp.async.bulk.tensor.2d.shared::cluster.global.mbarrier::complete_tx::bytes.multicast::cluster [%0], [%1, {%3, %4}], [%2], %5;"
    :: "r"(dst), "l"(tm), "r"(bar), "r"(c0), "r"(c1), "h"(mask) : "memory");
}
__device__ __forceinline__ void tma_load_3d(uint32_t dst, const CUtensorMap* tm, uint32_t bar, int c0, int c1, int c2) {
  asm volatile("cp.async.bulk.tensor.3d.shared::cluster.global.mbarrier::complete_tx::bytes [%0], [%1, {%3, %4, %5}], [%2];"
    :: "r"(dst), "l"(tm), "r"(bar), "r"(c0), "r"(c1), "r"(c2) : "memory");
}
__device__ __forceinline__ void tma_store_2d(const CUtensorMap* tm, uint32_t src, int c0, int c1) {
  asm volatile("cp.async.bulk.tensor.2d.global.shared::cta.bulk_group [%0, {%2, %3}], [%1];" :: "l"(tm), "r"(src), "r"(c0), "r"(c1) : "memory");
}
__device__ __forceinline__ void bulk_commit() { asm volatile("cp.async.bulk.commit_group;" ::: "memory"); }
__device__ __forceinline__ void bulk_wait_read0() { asm volatile("cp.async.bulk.wait_group.read 0;" ::: "memory"); }
__device__ __forceinline__ void bulk_wait0() { asm volatile("cp.async.bulk.wait_group 0;" ::: "memory"); }
__device__ __forceinline__ void fence_async() { asm volatile("fence.proxy.async;" ::: "memory"); }
__device__ __forceinline__ void fence_async_smem() { asm volatile("fence.proxy.async.shared::cta;" ::: "memory"); }
__device__ __forceinline__ void prefetch_tmap(const CUtensorMap* tm) { asm volatile("prefetch.tensormap [%0];" :: "l"(tm) : "memory"); }
__device__ __forceinline__ void wgmma_fence() { asm volatile("wgmma.fence.sync.aligned;" ::: "memory"); }
__device__ __forceinline__ void wgmma_commit() { asm volatile("wgmma.commit_group.sync.aligned;" ::: "memory"); }
template<int N> __device__ __forceinline__ void wgmma_wait() { asm volatile("wgmma.wait_group.sync.aligned %0;" :: "n"(N) : "memory"); }
__device__ __forceinline__ uint32_t desc_lo(uint32_t addr, uint32_t lbo) { return (addr >> 4) | ((lbo >> 4) << 16); }
constexpr uint32_t H128 = 0x40000040u, H64 = 0x80000020u;
__device__ __forceinline__ void cluster_sync() {
  asm volatile("barrier.cluster.arrive.release.aligned;\nbarrier.cluster.wait.acquire.aligned;" ::: "memory");
}
__device__ __forceinline__ uint64_t gtimer() { uint64_t t; asm volatile("mov.u64 %0, %%globaltimer;" : "=l"(t)); return t; }
template<int R> __device__ __forceinline__ void reg_alloc() { asm volatile("setmaxnreg.inc.sync.aligned.u32 %0;" :: "n"(R)); }
template<int R> __device__ __forceinline__ void reg_dealloc() { asm volatile("setmaxnreg.dec.sync.aligned.u32 %0;" :: "n"(R)); }
__device__ __forceinline__ void bar_sync(int id, int n) { asm volatile("bar.sync %0, %1;" :: "r"(id), "r"(n) : "memory"); }
__device__ __forceinline__ uint32_t pack_bf16(float lo, float hi) { uint32_t r; asm("cvt.rn.bf16x2.f32 %0, %1, %2;" : "=r"(r) : "f"(hi), "f"(lo)); return r; }
__device__ __forceinline__ float bf_lo(uint32_t v) { return __uint_as_float(v << 16); }
__device__ __forceinline__ float bf_hi(uint32_t v) { return __uint_as_float(v & 0xffff0000u); }
__device__ __forceinline__ float bf_round(float v) { return bf_lo(pack_bf16(v, 0.f)); }
__device__ __forceinline__ void stmatrix_x4(uint32_t addr, uint32_t r0, uint32_t r1, uint32_t r2, uint32_t r3) {
  asm volatile("stmatrix.sync.aligned.m8n8.x4.shared.b16 [%0], {%1, %2, %3, %4};" :: "r"(addr), "r"(r0), "r"(r1), "r"(r2), "r"(r3) : "memory");
}
__device__ __forceinline__ void ldmatrix_x4(uint32_t addr, uint32_t& r0, uint32_t& r1, uint32_t& r2, uint32_t& r3) {
  asm volatile("ldmatrix.sync.aligned.m8n8.x4.shared.b16 {%0, %1, %2, %3}, [%4];" : "=r"(r0), "=r"(r1), "=r"(r2), "=r"(r3) : "r"(addr) : "memory");
}
__device__ __forceinline__ uint32_t ld_acquire(const uint32_t* p) { uint32_t v; asm volatile("ld.acquire.gpu.global.u32 %0, [%1];" : "=r"(v) : "l"(p) : "memory"); return v; }
__device__ __forceinline__ uint32_t ld_relaxed(const uint32_t* p) { uint32_t v; asm volatile("ld.relaxed.gpu.global.u32 %0, [%1];" : "=r"(v) : "l"(p) : "memory"); return v; }
__device__ __forceinline__ void st_release(uint32_t* p, uint32_t v) { asm volatile("st.release.gpu.global.u32 [%0], %1;" :: "l"(p), "r"(v) : "memory"); }
__device__ __forceinline__ uint4 ld_vol4(const void* p) { uint4 v; asm volatile("ld.volatile.global.v4.u32 {%0, %1, %2, %3}, [%4];" : "=r"(v.x), "=r"(v.y), "=r"(v.z), "=r"(v.w) : "l"(p) : "memory"); return v; }
__device__ __forceinline__ uint2 ld_vol2(const void* p) { uint2 v; asm volatile("ld.volatile.global.v2.u32 {%0, %1}, [%2];" : "=r"(v.x), "=r"(v.y) : "l"(p) : "memory"); return v; }
__device__ __forceinline__ void st_vol2(void* p, uint32_t a, uint32_t b) { asm volatile("st.volatile.global.v2.u32 [%0], {%1, %2};" :: "l"(p), "r"(a), "r"(b) : "memory"); }
__device__ __forceinline__ void st_vol4(void* p, uint32_t a, uint32_t b, uint32_t c, uint32_t d) { asm volatile("st.volatile.global.v4.u32 [%0], {%1, %2, %3, %4};" :: "l"(p), "r"(a), "r"(b), "r"(c), "r"(d) : "memory"); }
__device__ __forceinline__ uint4 ld_nc4(const void* p) { uint4 v; asm volatile("ld.global.nc.L1::no_allocate.v4.u32 {%0, %1, %2, %3}, [%4];" : "=r"(v.x), "=r"(v.y), "=r"(v.z), "=r"(v.w) : "l"(p)); return v; }
__device__ __forceinline__ uint32_t ld_nc1(const void* p) { uint32_t v; asm volatile("ld.global.nc.u32 %0, [%1];" : "=r"(v) : "l"(p)); return v; }
__device__ __forceinline__ void red_add4(float4* p, float a, float b, float c, float d) {
  asm volatile("red.global.add.v4.f32 [%0], {%1, %2, %3, %4};" :: "l"(p), "f"(a), "f"(b), "f"(c), "f"(d) : "memory");
}
__device__ __forceinline__ void sts4(uint32_t a, uint32_t x, uint32_t y, uint32_t z, uint32_t w) { asm volatile("st.shared.v4.u32 [%0], {%1, %2, %3, %4};" :: "r"(a), "r"(x), "r"(y), "r"(z), "r"(w) : "memory"); }
__device__ __forceinline__ void sts2(uint32_t a, uint32_t x, uint32_t y) { asm volatile("st.shared.v2.u32 [%0], {%1, %2};" :: "r"(a), "r"(x), "r"(y) : "memory"); }
__device__ __forceinline__ void sts1(uint32_t a, uint32_t x) { asm volatile("st.shared.u32 [%0], %1;" :: "r"(a), "r"(x) : "memory"); }
__device__ __forceinline__ uint4 lds4(uint32_t a) { uint4 v; asm volatile("ld.shared.v4.u32 {%0, %1, %2, %3}, [%4];" : "=r"(v.x), "=r"(v.y), "=r"(v.z), "=r"(v.w) : "r"(a) : "memory"); return v; }
__device__ __forceinline__ uint2 lds2(uint32_t a) { uint2 v; asm volatile("ld.shared.v2.u32 {%0, %1}, [%2];" : "=r"(v.x), "=r"(v.y) : "r"(a) : "memory"); return v; }
__device__ __forceinline__ uint32_t lds1(uint32_t a) { uint32_t v; asm volatile("ld.shared.u32 %0, [%1];" : "=r"(v) : "r"(a) : "memory"); return v; }
__device__ __forceinline__ float ex2(float x) { float y; asm("ex2.approx.ftz.f32 %0, %1;" : "=f"(y) : "f"(x)); return y; }
__device__ __forceinline__ float rcp(float x) { float y; asm("rcp.approx.ftz.f32 %0, %1;" : "=f"(y) : "f"(x)); return y; }
__device__ __forceinline__ void prefetch_l2(const void* p) { asm volatile("prefetch.global.L2 [%0];" :: "l"(p)); }

__device__ __forceinline__ void st_relaxed(uint32_t* p, uint32_t v) { asm volatile("st.relaxed.gpu.global.u32 [%0], %1;" :: "l"(p), "r"(v) : "memory"); }
__device__ __forceinline__ uint4 ld_nc4p(const void* p) { uint4 v; asm volatile("ld.global.nc.L1::no_allocate.L2::128B.v4.u32 {%0, %1, %2, %3}, [%4];" : "=r"(v.x), "=r"(v.y), "=r"(v.z), "=r"(v.w) : "l"(p)); return v; }
__device__ __forceinline__ uint32_t mapa(uint32_t a, uint32_t cta) { uint32_t r; asm("mapa.shared::cluster.u32 %0, %1, %2;" : "=r"(r) : "r"(a), "r"(cta)); return r; }
__device__ __forceinline__ void mbar_arrive_cl(uint32_t a) { asm volatile("mbarrier.arrive.shared::cluster.b64 _, [%0];" :: "r"(a) : "memory"); }
__device__ __forceinline__ void bulk_load_mc(uint32_t dst, const void* src, uint32_t bytes, uint32_t bar) {
  asm volatile("cp.async.bulk.shared::cluster.global.mbarrier::complete_tx::bytes.multicast::cluster [%0], [%1], %2, [%3], %4;"
    :: "r"(dst), "l"(src), "r"(bytes), "r"(bar), "h"((uint16_t)3) : "memory");
}
__device__ __forceinline__ void bulk_store(void* dst, uint32_t src, uint32_t bytes) {
  asm volatile("cp.async.bulk.global.shared::cta.bulk_group [%0], [%1], %2;" :: "l"(dst), "r"(src), "r"(bytes) : "memory");
}
__device__ __forceinline__ void bulk_copy_peer(uint32_t dst, uint32_t src, uint32_t bytes, uint32_t bar) {
  asm volatile("cp.async.bulk.shared::cluster.shared::cta.mbarrier::complete_tx::bytes [%0], [%1], %2, [%3];" :: "r"(dst), "r"(src), "r"(bytes), "r"(bar) : "memory");
}
__device__ __forceinline__ void bulk_prefetch(const void* src, uint32_t bytes) { asm volatile("cp.async.bulk.prefetch.L2.global [%0], %1;" :: "l"(src), "r"(bytes) : "memory"); }
__device__ __forceinline__ void bulk_wait1() { asm volatile("cp.async.bulk.wait_group 1;" ::: "memory"); }
__device__ __forceinline__ void cluster_arrive() { asm volatile("barrier.cluster.arrive.relaxed.aligned;" ::: "memory"); }
__device__ __forceinline__ void cluster_wait() { asm volatile("barrier.cluster.wait.aligned;" ::: "memory"); }
__device__ __forceinline__ uint32_t hfma2(uint32_t a, uint32_t b, uint32_t c) { uint32_t r; asm("fma.rn.bf16x2 %0, %1, %2, %3;" : "=r"(r) : "r"(a), "r"(b), "r"(c)); return r; }
__device__ __forceinline__ uint32_t hmul2(uint32_t a, uint32_t b) { uint32_t r; asm("mul.rn.bf16x2 %0, %1, %2;" : "=r"(r) : "r"(a), "r"(b)); return r; }
template<int N> __device__ __forceinline__ void fence_regs(float (&r)[N]) {
#pragma unroll
  for (int i = 0; i < N; i++) asm volatile("" : "+f"(r[i]) :: "memory");
}

template<int TA, int TB, uint32_t HI> __device__ __forceinline__ void wgmma_ss_n192(float (&d)[96], uint32_t da, uint32_t db) {
  asm volatile("{\n.reg .pred p;\n.reg .b64 da, db;\nsetp.ne.b32 p, 1, 0;\nmov.b64 da, {%96, %100};\nmov.b64 db, {%97, %100};\n"
    "wgmma.mma_async.sync.aligned.m64n192k16.f32.bf16.bf16 {%0, %1, %2, %3, %4, %5, %6, %7, %8, %9, %10, %11, %12, %13, %14, %15, %16, %17, %18, %19, %20, %21, %22, %23, %24, %25, %26, %27, %28, %29, %30, %31, %32, %33, %34, %35, %36, %37, %38, %39, %40, %41, %42, %43, %44, %45, %46, %47, %48, %49, %50, %51, %52, %53, %54, %55, %56, %57, %58, %59, %60, %61, %62, %63, %64, %65, %66, %67, %68, %69, %70, %71, %72, %73, %74, %75, %76, %77, %78, %79, %80, %81, %82, %83, %84, %85, %86, %87, %88, %89, %90, %91, %92, %93, %94, %95}, da, db, p, 1, 1, %98, %99;\n}\n"
    : "+f"(d[0]), "+f"(d[1]), "+f"(d[2]), "+f"(d[3]), "+f"(d[4]), "+f"(d[5]), "+f"(d[6]), "+f"(d[7]), "+f"(d[8]), "+f"(d[9]), "+f"(d[10]), "+f"(d[11]), "+f"(d[12]), "+f"(d[13]), "+f"(d[14]), "+f"(d[15]), "+f"(d[16]), "+f"(d[17]), "+f"(d[18]), "+f"(d[19]), "+f"(d[20]), "+f"(d[21]), "+f"(d[22]), "+f"(d[23]), "+f"(d[24]), "+f"(d[25]), "+f"(d[26]), "+f"(d[27]), "+f"(d[28]), "+f"(d[29]), "+f"(d[30]), "+f"(d[31]), "+f"(d[32]), "+f"(d[33]), "+f"(d[34]), "+f"(d[35]), "+f"(d[36]), "+f"(d[37]), "+f"(d[38]), "+f"(d[39]), "+f"(d[40]), "+f"(d[41]), "+f"(d[42]), "+f"(d[43]), "+f"(d[44]), "+f"(d[45]), "+f"(d[46]), "+f"(d[47]), "+f"(d[48]), "+f"(d[49]), "+f"(d[50]), "+f"(d[51]), "+f"(d[52]), "+f"(d[53]), "+f"(d[54]), "+f"(d[55]), "+f"(d[56]), "+f"(d[57]), "+f"(d[58]), "+f"(d[59]), "+f"(d[60]), "+f"(d[61]), "+f"(d[62]), "+f"(d[63]), "+f"(d[64]), "+f"(d[65]), "+f"(d[66]), "+f"(d[67]), "+f"(d[68]), "+f"(d[69]), "+f"(d[70]), "+f"(d[71]), "+f"(d[72]), "+f"(d[73]), "+f"(d[74]), "+f"(d[75]), "+f"(d[76]), "+f"(d[77]), "+f"(d[78]), "+f"(d[79]), "+f"(d[80]), "+f"(d[81]), "+f"(d[82]), "+f"(d[83]), "+f"(d[84]), "+f"(d[85]), "+f"(d[86]), "+f"(d[87]), "+f"(d[88]), "+f"(d[89]), "+f"(d[90]), "+f"(d[91]), "+f"(d[92]), "+f"(d[93]), "+f"(d[94]), "+f"(d[95])
    : "r"(da), "r"(db), "n"(TA), "n"(TB), "n"(HI));
}
template<int TA, int TB, uint32_t HI> __device__ __forceinline__ void wgmma_ssz_n192(float (&d)[96], uint32_t da, uint32_t db) {
  asm volatile("{\n.reg .pred p;\n.reg .b64 da, db;\nsetp.ne.b32 p, 0, 0;\nmov.b64 da, {%96, %100};\nmov.b64 db, {%97, %100};\n"
    "wgmma.mma_async.sync.aligned.m64n192k16.f32.bf16.bf16 {%0, %1, %2, %3, %4, %5, %6, %7, %8, %9, %10, %11, %12, %13, %14, %15, %16, %17, %18, %19, %20, %21, %22, %23, %24, %25, %26, %27, %28, %29, %30, %31, %32, %33, %34, %35, %36, %37, %38, %39, %40, %41, %42, %43, %44, %45, %46, %47, %48, %49, %50, %51, %52, %53, %54, %55, %56, %57, %58, %59, %60, %61, %62, %63, %64, %65, %66, %67, %68, %69, %70, %71, %72, %73, %74, %75, %76, %77, %78, %79, %80, %81, %82, %83, %84, %85, %86, %87, %88, %89, %90, %91, %92, %93, %94, %95}, da, db, p, 1, 1, %98, %99;\n}\n"
    : "=f"(d[0]), "=f"(d[1]), "=f"(d[2]), "=f"(d[3]), "=f"(d[4]), "=f"(d[5]), "=f"(d[6]), "=f"(d[7]), "=f"(d[8]), "=f"(d[9]), "=f"(d[10]), "=f"(d[11]), "=f"(d[12]), "=f"(d[13]), "=f"(d[14]), "=f"(d[15]), "=f"(d[16]), "=f"(d[17]), "=f"(d[18]), "=f"(d[19]), "=f"(d[20]), "=f"(d[21]), "=f"(d[22]), "=f"(d[23]), "=f"(d[24]), "=f"(d[25]), "=f"(d[26]), "=f"(d[27]), "=f"(d[28]), "=f"(d[29]), "=f"(d[30]), "=f"(d[31]), "=f"(d[32]), "=f"(d[33]), "=f"(d[34]), "=f"(d[35]), "=f"(d[36]), "=f"(d[37]), "=f"(d[38]), "=f"(d[39]), "=f"(d[40]), "=f"(d[41]), "=f"(d[42]), "=f"(d[43]), "=f"(d[44]), "=f"(d[45]), "=f"(d[46]), "=f"(d[47]), "=f"(d[48]), "=f"(d[49]), "=f"(d[50]), "=f"(d[51]), "=f"(d[52]), "=f"(d[53]), "=f"(d[54]), "=f"(d[55]), "=f"(d[56]), "=f"(d[57]), "=f"(d[58]), "=f"(d[59]), "=f"(d[60]), "=f"(d[61]), "=f"(d[62]), "=f"(d[63]), "=f"(d[64]), "=f"(d[65]), "=f"(d[66]), "=f"(d[67]), "=f"(d[68]), "=f"(d[69]), "=f"(d[70]), "=f"(d[71]), "=f"(d[72]), "=f"(d[73]), "=f"(d[74]), "=f"(d[75]), "=f"(d[76]), "=f"(d[77]), "=f"(d[78]), "=f"(d[79]), "=f"(d[80]), "=f"(d[81]), "=f"(d[82]), "=f"(d[83]), "=f"(d[84]), "=f"(d[85]), "=f"(d[86]), "=f"(d[87]), "=f"(d[88]), "=f"(d[89]), "=f"(d[90]), "=f"(d[91]), "=f"(d[92]), "=f"(d[93]), "=f"(d[94]), "=f"(d[95])
    : "r"(da), "r"(db), "n"(TA), "n"(TB), "n"(HI));
}
template<int TA, int TB, uint32_t HI> __device__ __forceinline__ void wgmma_ss_n128(float (&d)[64], uint32_t da, uint32_t db) {
  asm volatile("{\n.reg .pred p;\n.reg .b64 da, db;\nsetp.ne.b32 p, 1, 0;\nmov.b64 da, {%64, %68};\nmov.b64 db, {%65, %68};\n"
    "wgmma.mma_async.sync.aligned.m64n128k16.f32.bf16.bf16 {%0, %1, %2, %3, %4, %5, %6, %7, %8, %9, %10, %11, %12, %13, %14, %15, %16, %17, %18, %19, %20, %21, %22, %23, %24, %25, %26, %27, %28, %29, %30, %31, %32, %33, %34, %35, %36, %37, %38, %39, %40, %41, %42, %43, %44, %45, %46, %47, %48, %49, %50, %51, %52, %53, %54, %55, %56, %57, %58, %59, %60, %61, %62, %63}, da, db, p, 1, 1, %66, %67;\n}\n"
    : "+f"(d[0]), "+f"(d[1]), "+f"(d[2]), "+f"(d[3]), "+f"(d[4]), "+f"(d[5]), "+f"(d[6]), "+f"(d[7]), "+f"(d[8]), "+f"(d[9]), "+f"(d[10]), "+f"(d[11]), "+f"(d[12]), "+f"(d[13]), "+f"(d[14]), "+f"(d[15]), "+f"(d[16]), "+f"(d[17]), "+f"(d[18]), "+f"(d[19]), "+f"(d[20]), "+f"(d[21]), "+f"(d[22]), "+f"(d[23]), "+f"(d[24]), "+f"(d[25]), "+f"(d[26]), "+f"(d[27]), "+f"(d[28]), "+f"(d[29]), "+f"(d[30]), "+f"(d[31]), "+f"(d[32]), "+f"(d[33]), "+f"(d[34]), "+f"(d[35]), "+f"(d[36]), "+f"(d[37]), "+f"(d[38]), "+f"(d[39]), "+f"(d[40]), "+f"(d[41]), "+f"(d[42]), "+f"(d[43]), "+f"(d[44]), "+f"(d[45]), "+f"(d[46]), "+f"(d[47]), "+f"(d[48]), "+f"(d[49]), "+f"(d[50]), "+f"(d[51]), "+f"(d[52]), "+f"(d[53]), "+f"(d[54]), "+f"(d[55]), "+f"(d[56]), "+f"(d[57]), "+f"(d[58]), "+f"(d[59]), "+f"(d[60]), "+f"(d[61]), "+f"(d[62]), "+f"(d[63])
    : "r"(da), "r"(db), "n"(TA), "n"(TB), "n"(HI));
}
template<int TA, int TB, uint32_t HI> __device__ __forceinline__ void wgmma_ssz_n128(float (&d)[64], uint32_t da, uint32_t db) {
  asm volatile("{\n.reg .pred p;\n.reg .b64 da, db;\nsetp.ne.b32 p, 0, 0;\nmov.b64 da, {%64, %68};\nmov.b64 db, {%65, %68};\n"
    "wgmma.mma_async.sync.aligned.m64n128k16.f32.bf16.bf16 {%0, %1, %2, %3, %4, %5, %6, %7, %8, %9, %10, %11, %12, %13, %14, %15, %16, %17, %18, %19, %20, %21, %22, %23, %24, %25, %26, %27, %28, %29, %30, %31, %32, %33, %34, %35, %36, %37, %38, %39, %40, %41, %42, %43, %44, %45, %46, %47, %48, %49, %50, %51, %52, %53, %54, %55, %56, %57, %58, %59, %60, %61, %62, %63}, da, db, p, 1, 1, %66, %67;\n}\n"
    : "=f"(d[0]), "=f"(d[1]), "=f"(d[2]), "=f"(d[3]), "=f"(d[4]), "=f"(d[5]), "=f"(d[6]), "=f"(d[7]), "=f"(d[8]), "=f"(d[9]), "=f"(d[10]), "=f"(d[11]), "=f"(d[12]), "=f"(d[13]), "=f"(d[14]), "=f"(d[15]), "=f"(d[16]), "=f"(d[17]), "=f"(d[18]), "=f"(d[19]), "=f"(d[20]), "=f"(d[21]), "=f"(d[22]), "=f"(d[23]), "=f"(d[24]), "=f"(d[25]), "=f"(d[26]), "=f"(d[27]), "=f"(d[28]), "=f"(d[29]), "=f"(d[30]), "=f"(d[31]), "=f"(d[32]), "=f"(d[33]), "=f"(d[34]), "=f"(d[35]), "=f"(d[36]), "=f"(d[37]), "=f"(d[38]), "=f"(d[39]), "=f"(d[40]), "=f"(d[41]), "=f"(d[42]), "=f"(d[43]), "=f"(d[44]), "=f"(d[45]), "=f"(d[46]), "=f"(d[47]), "=f"(d[48]), "=f"(d[49]), "=f"(d[50]), "=f"(d[51]), "=f"(d[52]), "=f"(d[53]), "=f"(d[54]), "=f"(d[55]), "=f"(d[56]), "=f"(d[57]), "=f"(d[58]), "=f"(d[59]), "=f"(d[60]), "=f"(d[61]), "=f"(d[62]), "=f"(d[63])
    : "r"(da), "r"(db), "n"(TA), "n"(TB), "n"(HI));
}
template<int TA, int TB, uint32_t HI> __device__ __forceinline__ void wgmma_ss_n40(float (&d)[20], uint32_t da, uint32_t db) {
  asm volatile("{\n.reg .pred p;\n.reg .b64 da, db;\nsetp.ne.b32 p, 1, 0;\nmov.b64 da, {%20, %24};\nmov.b64 db, {%21, %24};\n"
    "wgmma.mma_async.sync.aligned.m64n40k16.f32.bf16.bf16 {%0, %1, %2, %3, %4, %5, %6, %7, %8, %9, %10, %11, %12, %13, %14, %15, %16, %17, %18, %19}, da, db, p, 1, 1, %22, %23;\n}\n"
    : "+f"(d[0]), "+f"(d[1]), "+f"(d[2]), "+f"(d[3]), "+f"(d[4]), "+f"(d[5]), "+f"(d[6]), "+f"(d[7]), "+f"(d[8]), "+f"(d[9]), "+f"(d[10]), "+f"(d[11]), "+f"(d[12]), "+f"(d[13]), "+f"(d[14]), "+f"(d[15]), "+f"(d[16]), "+f"(d[17]), "+f"(d[18]), "+f"(d[19])
    : "r"(da), "r"(db), "n"(TA), "n"(TB), "n"(HI));
}
template<int TA, int TB, uint32_t HI> __device__ __forceinline__ void wgmma_ssz_n40(float (&d)[20], uint32_t da, uint32_t db) {
  asm volatile("{\n.reg .pred p;\n.reg .b64 da, db;\nsetp.ne.b32 p, 0, 0;\nmov.b64 da, {%20, %24};\nmov.b64 db, {%21, %24};\n"
    "wgmma.mma_async.sync.aligned.m64n40k16.f32.bf16.bf16 {%0, %1, %2, %3, %4, %5, %6, %7, %8, %9, %10, %11, %12, %13, %14, %15, %16, %17, %18, %19}, da, db, p, 1, 1, %22, %23;\n}\n"
    : "=f"(d[0]), "=f"(d[1]), "=f"(d[2]), "=f"(d[3]), "=f"(d[4]), "=f"(d[5]), "=f"(d[6]), "=f"(d[7]), "=f"(d[8]), "=f"(d[9]), "=f"(d[10]), "=f"(d[11]), "=f"(d[12]), "=f"(d[13]), "=f"(d[14]), "=f"(d[15]), "=f"(d[16]), "=f"(d[17]), "=f"(d[18]), "=f"(d[19])
    : "r"(da), "r"(db), "n"(TA), "n"(TB), "n"(HI));
}
template<int TB, uint32_t HI> __device__ __forceinline__ void wgmma_rs_n256(float (&d)[128], uint32_t a0, uint32_t a1, uint32_t a2, uint32_t a3, uint32_t db) {
  asm volatile("{\n.reg .pred p;\n.reg .b64 db;\nsetp.ne.b32 p, 1, 0;\nmov.b64 db, {%132, %134};\n"
    "wgmma.mma_async.sync.aligned.m64n256k16.f32.bf16.bf16 {%0, %1, %2, %3, %4, %5, %6, %7, %8, %9, %10, %11, %12, %13, %14, %15, %16, %17, %18, %19, %20, %21, %22, %23, %24, %25, %26, %27, %28, %29, %30, %31, %32, %33, %34, %35, %36, %37, %38, %39, %40, %41, %42, %43, %44, %45, %46, %47, %48, %49, %50, %51, %52, %53, %54, %55, %56, %57, %58, %59, %60, %61, %62, %63, %64, %65, %66, %67, %68, %69, %70, %71, %72, %73, %74, %75, %76, %77, %78, %79, %80, %81, %82, %83, %84, %85, %86, %87, %88, %89, %90, %91, %92, %93, %94, %95, %96, %97, %98, %99, %100, %101, %102, %103, %104, %105, %106, %107, %108, %109, %110, %111, %112, %113, %114, %115, %116, %117, %118, %119, %120, %121, %122, %123, %124, %125, %126, %127}, {%128, %129, %130, %131}, db, p, 1, 1, %133;\n}\n"
    : "+f"(d[0]), "+f"(d[1]), "+f"(d[2]), "+f"(d[3]), "+f"(d[4]), "+f"(d[5]), "+f"(d[6]), "+f"(d[7]), "+f"(d[8]), "+f"(d[9]), "+f"(d[10]), "+f"(d[11]), "+f"(d[12]), "+f"(d[13]), "+f"(d[14]), "+f"(d[15]), "+f"(d[16]), "+f"(d[17]), "+f"(d[18]), "+f"(d[19]), "+f"(d[20]), "+f"(d[21]), "+f"(d[22]), "+f"(d[23]), "+f"(d[24]), "+f"(d[25]), "+f"(d[26]), "+f"(d[27]), "+f"(d[28]), "+f"(d[29]), "+f"(d[30]), "+f"(d[31]), "+f"(d[32]), "+f"(d[33]), "+f"(d[34]), "+f"(d[35]), "+f"(d[36]), "+f"(d[37]), "+f"(d[38]), "+f"(d[39]), "+f"(d[40]), "+f"(d[41]), "+f"(d[42]), "+f"(d[43]), "+f"(d[44]), "+f"(d[45]), "+f"(d[46]), "+f"(d[47]), "+f"(d[48]), "+f"(d[49]), "+f"(d[50]), "+f"(d[51]), "+f"(d[52]), "+f"(d[53]), "+f"(d[54]), "+f"(d[55]), "+f"(d[56]), "+f"(d[57]), "+f"(d[58]), "+f"(d[59]), "+f"(d[60]), "+f"(d[61]), "+f"(d[62]), "+f"(d[63]), "+f"(d[64]), "+f"(d[65]), "+f"(d[66]), "+f"(d[67]), "+f"(d[68]), "+f"(d[69]), "+f"(d[70]), "+f"(d[71]), "+f"(d[72]), "+f"(d[73]), "+f"(d[74]), "+f"(d[75]), "+f"(d[76]), "+f"(d[77]), "+f"(d[78]), "+f"(d[79]), "+f"(d[80]), "+f"(d[81]), "+f"(d[82]), "+f"(d[83]), "+f"(d[84]), "+f"(d[85]), "+f"(d[86]), "+f"(d[87]), "+f"(d[88]), "+f"(d[89]), "+f"(d[90]), "+f"(d[91]), "+f"(d[92]), "+f"(d[93]), "+f"(d[94]), "+f"(d[95]), "+f"(d[96]), "+f"(d[97]), "+f"(d[98]), "+f"(d[99]), "+f"(d[100]), "+f"(d[101]), "+f"(d[102]), "+f"(d[103]), "+f"(d[104]), "+f"(d[105]), "+f"(d[106]), "+f"(d[107]), "+f"(d[108]), "+f"(d[109]), "+f"(d[110]), "+f"(d[111]), "+f"(d[112]), "+f"(d[113]), "+f"(d[114]), "+f"(d[115]), "+f"(d[116]), "+f"(d[117]), "+f"(d[118]), "+f"(d[119]), "+f"(d[120]), "+f"(d[121]), "+f"(d[122]), "+f"(d[123]), "+f"(d[124]), "+f"(d[125]), "+f"(d[126]), "+f"(d[127])
    : "r"(a0), "r"(a1), "r"(a2), "r"(a3), "r"(db), "n"(TB), "n"(HI));
}
template<int TB, uint32_t HI> __device__ __forceinline__ void wgmma_rsz_n256(float (&d)[128], uint32_t a0, uint32_t a1, uint32_t a2, uint32_t a3, uint32_t db) {
  asm volatile("{\n.reg .pred p;\n.reg .b64 db;\nsetp.ne.b32 p, 0, 0;\nmov.b64 db, {%132, %134};\n"
    "wgmma.mma_async.sync.aligned.m64n256k16.f32.bf16.bf16 {%0, %1, %2, %3, %4, %5, %6, %7, %8, %9, %10, %11, %12, %13, %14, %15, %16, %17, %18, %19, %20, %21, %22, %23, %24, %25, %26, %27, %28, %29, %30, %31, %32, %33, %34, %35, %36, %37, %38, %39, %40, %41, %42, %43, %44, %45, %46, %47, %48, %49, %50, %51, %52, %53, %54, %55, %56, %57, %58, %59, %60, %61, %62, %63, %64, %65, %66, %67, %68, %69, %70, %71, %72, %73, %74, %75, %76, %77, %78, %79, %80, %81, %82, %83, %84, %85, %86, %87, %88, %89, %90, %91, %92, %93, %94, %95, %96, %97, %98, %99, %100, %101, %102, %103, %104, %105, %106, %107, %108, %109, %110, %111, %112, %113, %114, %115, %116, %117, %118, %119, %120, %121, %122, %123, %124, %125, %126, %127}, {%128, %129, %130, %131}, db, p, 1, 1, %133;\n}\n"
    : "=f"(d[0]), "=f"(d[1]), "=f"(d[2]), "=f"(d[3]), "=f"(d[4]), "=f"(d[5]), "=f"(d[6]), "=f"(d[7]), "=f"(d[8]), "=f"(d[9]), "=f"(d[10]), "=f"(d[11]), "=f"(d[12]), "=f"(d[13]), "=f"(d[14]), "=f"(d[15]), "=f"(d[16]), "=f"(d[17]), "=f"(d[18]), "=f"(d[19]), "=f"(d[20]), "=f"(d[21]), "=f"(d[22]), "=f"(d[23]), "=f"(d[24]), "=f"(d[25]), "=f"(d[26]), "=f"(d[27]), "=f"(d[28]), "=f"(d[29]), "=f"(d[30]), "=f"(d[31]), "=f"(d[32]), "=f"(d[33]), "=f"(d[34]), "=f"(d[35]), "=f"(d[36]), "=f"(d[37]), "=f"(d[38]), "=f"(d[39]), "=f"(d[40]), "=f"(d[41]), "=f"(d[42]), "=f"(d[43]), "=f"(d[44]), "=f"(d[45]), "=f"(d[46]), "=f"(d[47]), "=f"(d[48]), "=f"(d[49]), "=f"(d[50]), "=f"(d[51]), "=f"(d[52]), "=f"(d[53]), "=f"(d[54]), "=f"(d[55]), "=f"(d[56]), "=f"(d[57]), "=f"(d[58]), "=f"(d[59]), "=f"(d[60]), "=f"(d[61]), "=f"(d[62]), "=f"(d[63]), "=f"(d[64]), "=f"(d[65]), "=f"(d[66]), "=f"(d[67]), "=f"(d[68]), "=f"(d[69]), "=f"(d[70]), "=f"(d[71]), "=f"(d[72]), "=f"(d[73]), "=f"(d[74]), "=f"(d[75]), "=f"(d[76]), "=f"(d[77]), "=f"(d[78]), "=f"(d[79]), "=f"(d[80]), "=f"(d[81]), "=f"(d[82]), "=f"(d[83]), "=f"(d[84]), "=f"(d[85]), "=f"(d[86]), "=f"(d[87]), "=f"(d[88]), "=f"(d[89]), "=f"(d[90]), "=f"(d[91]), "=f"(d[92]), "=f"(d[93]), "=f"(d[94]), "=f"(d[95]), "=f"(d[96]), "=f"(d[97]), "=f"(d[98]), "=f"(d[99]), "=f"(d[100]), "=f"(d[101]), "=f"(d[102]), "=f"(d[103]), "=f"(d[104]), "=f"(d[105]), "=f"(d[106]), "=f"(d[107]), "=f"(d[108]), "=f"(d[109]), "=f"(d[110]), "=f"(d[111]), "=f"(d[112]), "=f"(d[113]), "=f"(d[114]), "=f"(d[115]), "=f"(d[116]), "=f"(d[117]), "=f"(d[118]), "=f"(d[119]), "=f"(d[120]), "=f"(d[121]), "=f"(d[122]), "=f"(d[123]), "=f"(d[124]), "=f"(d[125]), "=f"(d[126]), "=f"(d[127])
    : "r"(a0), "r"(a1), "r"(a2), "r"(a3), "r"(db), "n"(TB), "n"(HI));
}
template<int TB, uint32_t HI> __device__ __forceinline__ void wgmma_rs_n40(float (&d)[20], uint32_t a0, uint32_t a1, uint32_t a2, uint32_t a3, uint32_t db) {
  asm volatile("{\n.reg .pred p;\n.reg .b64 db;\nsetp.ne.b32 p, 1, 0;\nmov.b64 db, {%24, %26};\n"
    "wgmma.mma_async.sync.aligned.m64n40k16.f32.bf16.bf16 {%0, %1, %2, %3, %4, %5, %6, %7, %8, %9, %10, %11, %12, %13, %14, %15, %16, %17, %18, %19}, {%20, %21, %22, %23}, db, p, 1, 1, %25;\n}\n"
    : "+f"(d[0]), "+f"(d[1]), "+f"(d[2]), "+f"(d[3]), "+f"(d[4]), "+f"(d[5]), "+f"(d[6]), "+f"(d[7]), "+f"(d[8]), "+f"(d[9]), "+f"(d[10]), "+f"(d[11]), "+f"(d[12]), "+f"(d[13]), "+f"(d[14]), "+f"(d[15]), "+f"(d[16]), "+f"(d[17]), "+f"(d[18]), "+f"(d[19])
    : "r"(a0), "r"(a1), "r"(a2), "r"(a3), "r"(db), "n"(TB), "n"(HI));
}
template<int TB, uint32_t HI> __device__ __forceinline__ void wgmma_rsz_n40(float (&d)[20], uint32_t a0, uint32_t a1, uint32_t a2, uint32_t a3, uint32_t db) {
  asm volatile("{\n.reg .pred p;\n.reg .b64 db;\nsetp.ne.b32 p, 0, 0;\nmov.b64 db, {%24, %26};\n"
    "wgmma.mma_async.sync.aligned.m64n40k16.f32.bf16.bf16 {%0, %1, %2, %3, %4, %5, %6, %7, %8, %9, %10, %11, %12, %13, %14, %15, %16, %17, %18, %19}, {%20, %21, %22, %23}, db, p, 1, 1, %25;\n}\n"
    : "=f"(d[0]), "=f"(d[1]), "=f"(d[2]), "=f"(d[3]), "=f"(d[4]), "=f"(d[5]), "=f"(d[6]), "=f"(d[7]), "=f"(d[8]), "=f"(d[9]), "=f"(d[10]), "=f"(d[11]), "=f"(d[12]), "=f"(d[13]), "=f"(d[14]), "=f"(d[15]), "=f"(d[16]), "=f"(d[17]), "=f"(d[18]), "=f"(d[19])
    : "r"(a0), "r"(a1), "r"(a2), "r"(a3), "r"(db), "n"(TB), "n"(HI));
}
template<int TB, uint32_t HI> __device__ __forceinline__ void wgmma_rs_n32(float (&d)[16], uint32_t a0, uint32_t a1, uint32_t a2, uint32_t a3, uint32_t db) {
  asm volatile("{\n.reg .pred p;\n.reg .b64 db;\nsetp.ne.b32 p, 1, 0;\nmov.b64 db, {%20, %22};\n"
    "wgmma.mma_async.sync.aligned.m64n32k16.f32.bf16.bf16 {%0, %1, %2, %3, %4, %5, %6, %7, %8, %9, %10, %11, %12, %13, %14, %15}, {%16, %17, %18, %19}, db, p, 1, 1, %21;\n}\n"
    : "+f"(d[0]), "+f"(d[1]), "+f"(d[2]), "+f"(d[3]), "+f"(d[4]), "+f"(d[5]), "+f"(d[6]), "+f"(d[7]), "+f"(d[8]), "+f"(d[9]), "+f"(d[10]), "+f"(d[11]), "+f"(d[12]), "+f"(d[13]), "+f"(d[14]), "+f"(d[15])
    : "r"(a0), "r"(a1), "r"(a2), "r"(a3), "r"(db), "n"(TB), "n"(HI));
}
template<int TB, uint32_t HI> __device__ __forceinline__ void wgmma_rsz_n32(float (&d)[16], uint32_t a0, uint32_t a1, uint32_t a2, uint32_t a3, uint32_t db) {
  asm volatile("{\n.reg .pred p;\n.reg .b64 db;\nsetp.ne.b32 p, 0, 0;\nmov.b64 db, {%20, %22};\n"
    "wgmma.mma_async.sync.aligned.m64n32k16.f32.bf16.bf16 {%0, %1, %2, %3, %4, %5, %6, %7, %8, %9, %10, %11, %12, %13, %14, %15}, {%16, %17, %18, %19}, db, p, 1, 1, %21;\n}\n"
    : "=f"(d[0]), "=f"(d[1]), "=f"(d[2]), "=f"(d[3]), "=f"(d[4]), "=f"(d[5]), "=f"(d[6]), "=f"(d[7]), "=f"(d[8]), "=f"(d[9]), "=f"(d[10]), "=f"(d[11]), "=f"(d[12]), "=f"(d[13]), "=f"(d[14]), "=f"(d[15])
    : "r"(a0), "r"(a1), "r"(a2), "r"(a3), "r"(db), "n"(TB), "n"(HI));
}

template<int N, bool Z> __device__ __forceinline__ void wgmma_ss(float (&d)[N / 2], uint32_t da, uint32_t db) {
  if constexpr (Z) {
    if constexpr (N == 192) wgmma_ssz_n192<0, 1, H128>(d, da, db);
    else wgmma_ssz_n128<0, 1, H128>(d, da, db);
  } else {
    if constexpr (N == 192) wgmma_ss_n192<0, 1, H128>(d, da, db);
    else wgmma_ss_n128<0, 1, H128>(d, da, db);
  }
}
__device__ __forceinline__ void phi_mma(float (&d)[16], const uint32_t* a, uint32_t wphi) {
  wgmma_rsz_n32<1, H64>(d, a[0], a[1], a[2], a[3], desc_lo(wphi, 2048));
  wgmma_rs_n32<1, H64>(d, a[4], a[5], a[6], a[7], desc_lo(wphi + 1024, 2048));
}

constexpr int NJOBS = 7;
constexpr int NST = 16 * 6 + 56;
constexpr int J_KV = 0, J_Q = 16, J_WO = 32, J_F1A = 48, J_F1B = 64, J_F1C = 80, J_F2 = 96;
struct Sched { int off[NST]; int need[NST]; };
constexpr Sched make_sched() {
  Sched s{};
  const int sz[NJOBS] = {6, 4, 4, 4, 4, 5, 4};
  const int ns[NJOBS] = {16, 16, 16, 16, 16, 16, 56};
  int szs[NST] = {};
  int g = 0, off = 0;
  for (int j = 0; j < NJOBS; j++)
    for (int i = 0; i < ns[j]; i++) {
      if (off + sz[j] > 24) off = 0;
      if ((j == 1 || g == J_WO) && off == 4) off = 8;
      s.off[g] = off; szs[g] = sz[j];
      int need = g - 8;
      for (int p = g - 1; p >= 0 && p > g - 8; p--)
        if (s.off[p] < off + sz[j] && off < s.off[p] + szs[p]) { need = p; break; }
      s.need[g] = need;
      off += sz[j]; g++;
    }
  return s;
}
constexpr Sched SCH = make_sched();
constexpr uint64_t dpack(int g0, bool own) {
  uint64_t r = 0;
  for (int i = 0; i < 16; i++) {
    int need = SCH.need[g0 + i];
    if (own && i == 6 && need < g0 + 1) need = g0 + 1;
    if (own && i == 8 && need < g0 + 3) need = g0 + 3;
    r |= (uint64_t)(g0 + i - need) << (4 * i);
  }
  return r;
}
constexpr bool sched_ok() {
  for (int g = J_F2 + 15; g < NST; g++) if (g - SCH.need[g] != J_F2 + 15 - SCH.need[J_F2 + 15]) return false;
  return SCH.off[J_WO + 5] == 4 && SCH.off[J_WO + 6] == SCH.off[J_WO] && SCH.off[J_WO + 8] == SCH.off[J_WO + 2] &&
         SCH.off[J_F1A + 6] == SCH.off[J_F1A] && SCH.off[J_F1A + 8] == SCH.off[J_F1A + 2] && SCH.off[12] == 0 && SCH.off[13] == 6;
}
static_assert(sched_ok(), "schedule");
constexpr int LAST_REL = SCH.need[NST - 1];
template<int G0, bool OWN> constexpr uint64_t DPACK = dpack(G0, OWN);
template<int G> constexpr uint32_t OFF = SCH.off[G] * 8192;
template<int G> constexpr int NEED = SCH.need[G];

constexpr uint32_t SM_RING = 192 * 1024;
constexpr uint32_t SM_SCR = 32 * 1024;
constexpr uint32_t SM_MISC = SM_RING;
constexpr uint32_t SM_WPHI = SM_MISC;
constexpr uint32_t SM_STG = SM_MISC + 8192;
constexpr uint32_t SM_GS1 = SM_MISC + 24576;
constexpr uint32_t SM_GS2 = SM_MISC + 28672;
constexpr uint32_t SM_VEC = SM_MISC + 32768;
constexpr uint32_t SM_BAR = SM_MISC + 34816;
constexpr uint32_t SM_TOTAL = SM_MISC + 35840;
constexpr uint32_t B_FULL = SM_BAR, B_EMPTY = SM_BAR + 64, B_SCR = SM_BAR + 128, B_WPHI = SM_BAR + 136, B_VEC = SM_BAR + 144,
                   B_UT = SM_BAR + 152, B_GS1 = SM_BAR + 160, B_KV = SM_BAR + 168, B_T0 = SM_BAR + 176, B_T1 = SM_BAR + 184;
constexpr uint32_t SM_RED = SM_BAR + 256;

struct Params {
  CUtensorMap tm_x, tm_out, tm_wqkv, tm_wo, tm_w1a, tm_w1c, tm_w2, tm_wphi;
  const bf16 *x, *wqkv, *wo, *w1, *w2, *b1, *b2, *c, *wmod;
};

__device__ __forceinline__ float silu_bf(float v) { return bf_round(__fdividef(v, 1.f + __expf(-v))); }
__device__ __forceinline__ void wait_empty(uint32_t sb, int g) { mbar_wait(sb + B_EMPTY + 8 * (g & 7), (g >> 3) & 1); }

template<int SZ, bool SKIP> __device__ __forceinline__ uint32_t next_slot(uint32_t a, uint32_t sb) {
  a += SZ * 8192;
  if (a + SZ * 8192 > sb + SM_RING) a = sb;
  if (SKIP && a == sb + SM_SCR) a += 32768;
  return a;
}
template<int G0, int I0, int I1, int SZ, bool OWN, class F> __device__ __forceinline__ void prod_range(uint32_t sb, F&& f) {
  constexpr uint32_t off0 = OFF<G0 + I0>;
  constexpr uint64_t dp0 = DPACK<G0, OWN> >> (4 * (I0 < 15 ? I0 : 15));
  uint32_t a = sb + off0;
  uint64_t dp = dp0;
#pragma unroll 1
  for (int i = I0; i < I1; i++) {
    f(i, a, sb + B_FULL + 8 * ((G0 + i) & 7), G0 + i - (int)(dp & 15));
    if (i < 15) dp >>= 4;
    a = next_slot<SZ, G0 == J_Q>(a, sb);
  }
}
__device__ __forceinline__ int own_chunk(int i, int n) {
  if (i < 4) return 2 * (n ^ (i & 1)) + (i >> 1);
  int j = i - 4, odd = j >= 6;
  return 2 * (((n & 6) + 2 + j - odd * 6) & 7) + odd;
}

struct Ctx { uint32_t sb, ebase, stg, srow; int wg, tid, lane, w4; uint32_t epoch; };
struct Pipe { uint32_t g, a; };

__device__ __forceinline__ void release_stage(const Ctx& c, uint32_t g) { if (c.tid < 2) mbar_arrive_cl(c.ebase + 8 * (g & 7)); }
__device__ __forceinline__ void wait_full(const Ctx& c, const Pipe& p) { mbar_wait(c.sb + B_FULL + 8 * (p.g & 7), (p.g >> 3) & 1); }
template<int N, bool Z> __device__ __forceinline__ void mma4(const Ctx& c, float (&acc)[N / 2], const Pipe& p) {
  uint32_t da = desc_lo(p.a + c.wg * 8192, 0), db = desc_lo(p.a + 16384, 8192);
  wgmma_ss<N, Z>(acc, da, db);
#pragma unroll
  for (int k = 1; k < 4; k++) wgmma_ss<N, false>(acc, da + k * 2, db + k * 128);
}
template<int N, bool Z, bool SKIP, bool REL> __device__ __forceinline__ void step(const Ctx& c, Pipe& p, float (&acc)[N / 2]) {
  wait_full(c, p);
  wgmma_fence();
  mma4<N, Z>(c, acc, p);
  wgmma_commit();
  wgmma_wait<1>();
  if (REL) release_stage(c, p.g - 1);
  p.g++; p.a = next_slot<N == 192 ? 5 : 4, SKIP>(p.a, c.sb);
}

__device__ __forceinline__ void dual_softmax(const float (&p)[16], uint32_t (&ph)[16]) {
  constexpr float L2E = 1.4426950408889634f;
#pragma unroll
  for (int r = 0; r < 2; r++) {
    float mx = fmaxf(p[2 * r], p[2 * r + 1]), mn = fminf(p[2 * r], p[2 * r + 1]);
#pragma unroll
    for (int j = 1; j < 4; j++) { mx = fmaxf(mx, fmaxf(p[4 * j + 2 * r], p[4 * j + 2 * r + 1])); mn = fminf(mn, fminf(p[4 * j + 2 * r], p[4 * j + 2 * r + 1])); }
    mx = fmaxf(mx, __shfl_xor_sync(~0u, mx, 1)); mn = fminf(mn, __shfl_xor_sync(~0u, mn, 1));
    mx = fmaxf(mx, __shfl_xor_sync(~0u, mx, 2)); mn = fminf(mn, __shfl_xor_sync(~0u, mn, 2));
    float a = -mx * L2E, b = mn * L2E;
    float ep[8], en[8], sp = 0.f, sn = 0.f;
#pragma unroll
    for (int j = 0; j < 4; j++)
#pragma unroll
      for (int e = 0; e < 2; e++) {
        float v = p[4 * j + 2 * r + e];
        ep[2 * j + e] = ex2(fmaf(v, L2E, a)); en[2 * j + e] = ex2(fmaf(v, -L2E, b));
        sp += ep[2 * j + e]; sn += en[2 * j + e];
      }
    sp += __shfl_xor_sync(~0u, sp, 1); sn += __shfl_xor_sync(~0u, sn, 1);
    sp += __shfl_xor_sync(~0u, sp, 2); sn += __shfl_xor_sync(~0u, sn, 2);
    float ip = rcp(sp), in = rcp(sn);
#pragma unroll
    for (int j = 0; j < 4; j++) {
      ph[2 * j + r] = pack_bf16(ep[2 * j] * ip, ep[2 * j + 1] * ip);
      ph[8 + 2 * j + r] = pack_bf16(en[2 * j] * in, en[2 * j + 1] * in);
    }
  }
}

__device__ __forceinline__ uint32_t stm_addr(const Ctx& c, uint32_t base, int cb) { return base + (c.srow ^ (cb << 4)); }

__device__ __forceinline__ void stg_acquire(const Ctx& c) { if (c.lane == 0) bulk_wait_read0(); __syncwarp(); }
__device__ __forceinline__ void stg_store(const Ctx& c, uint8_t* dst) {
  fence_async_smem();
  __syncwarp();
  if (c.lane == 0) { bulk_store(dst, c.stg, 2048); bulk_commit(); }
}
__device__ __forceinline__ void warp_publish(const Ctx& c, uint32_t* flag) { if (c.lane == 0) { bulk_wait0(); st_relaxed(flag, c.epoch); } __syncwarp(); }

struct RowStat { float mu0, rs0, mu1, rs1; };
template<int N, int H> __device__ __forceinline__ void ffn1_half(const Ctx& c, float (&acc)[N / 2], int ucol, uint8_t* dst, const RowStat& s) {
  if (!(H & 1)) stg_acquire(c);
#pragma unroll
  for (int jj = 0; jj < 2; jj++) {
    uint32_t r[4];
#pragma unroll
    for (int e = 0; e < 2; e++) {
      int j = H * 4 + jj * 2 + e;
      uint4 ut = lds4(c.sb + SM_WPHI + (ucol + j * 8 + (c.lane & 3) * 2) * 8);
      float u0 = __uint_as_float(ut.x), t0 = __uint_as_float(ut.y), u1 = __uint_as_float(ut.z), t1 = __uint_as_float(ut.w);
      float z0 = fmaxf(fmaf(s.rs0, fmaf(-s.mu0, u0, acc[4 * j]), t0), 0.f), z1 = fmaxf(fmaf(s.rs0, fmaf(-s.mu0, u1, acc[4 * j + 1]), t1), 0.f);
      float z2 = fmaxf(fmaf(s.rs1, fmaf(-s.mu1, u0, acc[4 * j + 2]), t0), 0.f), z3 = fmaxf(fmaf(s.rs1, fmaf(-s.mu1, u1, acc[4 * j + 3]), t1), 0.f);
      r[2 * e] = pack_bf16(z0 * z0, z1 * z1); r[2 * e + 1] = pack_bf16(z2 * z2, z3 * z3);
    }
    stmatrix_x4(stm_addr(c, c.stg, (H & 1) * 4 + jj * 2), r[0], r[1], r[2], r[3]);
  }
  if (H & 1) stg_store(c, dst + (H >> 1) * 16384);
}

template<bool DUAL> __device__ __forceinline__ void gemv32(const bf16* w, int ld, uint32_t coef, uint32_t red, int ht, float& o0, float& o1) {
  constexpr int U = DUAL ? 4 : 8;
  int seg = ht & 3, r0 = ht >> 2;
  const bf16* wp = w + (size_t)r0 * ld + seg * 8;
  float a[8], b[8];
#pragma unroll
  for (int e = 0; e < 8; e++) { a[e] = 0.f; b[e] = 0.f; }
#pragma unroll 1
  for (int it = 0; it < 64 / U; it++) {
    uint4 v[U];
#pragma unroll
    for (int u = 0; u < U; u++) v[u] = ld_nc4(wp + (size_t)(it * U + u) * 16 * ld);
#pragma unroll
    for (int u = 0; u < U; u++) {
      uint32_t cf = lds1(coef + ((it * U + u) * 16 + r0) * 4);
      float c0 = bf_lo(cf), c1 = bf_hi(cf);
      uint32_t vv[4] = {v[u].x, v[u].y, v[u].z, v[u].w};
#pragma unroll
      for (int e = 0; e < 4; e++) {
        float lo = bf_lo(vv[e]), hi = bf_hi(vv[e]);
        a[2 * e] = fmaf(c0, lo, a[2 * e]); a[2 * e + 1] = fmaf(c0, hi, a[2 * e + 1]);
        if (DUAL) { b[2 * e] = fmaf(c1, lo, b[2 * e]); b[2 * e + 1] = fmaf(c1, hi, b[2 * e + 1]); }
      }
    }
  }
#pragma unroll
  for (int e = 0; e < 8; e++)
#pragma unroll
    for (int s = 4; s < 32; s <<= 1) { a[e] += __shfl_xor_sync(~0u, a[e], s); if (DUAL) b[e] += __shfl_xor_sync(~0u, b[e], s); }
  bar_sync(4, 64);
  if ((ht & 31) < 4) {
#pragma unroll
    for (int e = 0; e < 8; e++) sts2(red + ((ht >> 5) * 32 + seg * 8 + e) * 8, __float_as_uint(a[e]), __float_as_uint(b[e]));
  }
  bar_sync(4, 64);
  uint2 x0 = lds2(red + (ht & 31) * 8), x1 = lds2(red + (32 + (ht & 31)) * 8);
  o0 = __uint_as_float(x0.x) + __uint_as_float(x1.x); o1 = __uint_as_float(x0.y) + __uint_as_float(x1.y);
}

__device__ __forceinline__ uint4 poll4(const void* p, uint32_t epoch) {
  uint4 v; uint32_t n = 0;
  while (true) { v = ld_vol4(p); if (v.y == epoch && v.w == epoch) break; spin_guard(++n); }
  return v;
}
__device__ __forceinline__ void poll4x2(const void* p0, const void* p1, uint32_t epoch, uint4& v, uint4& w) {
  uint32_t n = 0;
  while (true) { v = ld_vol4(p0); w = ld_vol4(p1); if (v.y == epoch && v.w == epoch && w.y == epoch && w.w == epoch) break; spin_guard(++n); }
}
__device__ __forceinline__ uint2 poll2(const void* p, uint32_t epoch) {
  uint2 v; uint32_t n = 0;
  while (true) { v = ld_vol2(p); if (v.y == epoch) break; spin_guard(++n); }
  return v;
}
__device__ __forceinline__ void poll_flags(const uint32_t* flags, int lane, uint32_t epoch, uint32_t want, uint32_t& mask) {
  uint32_t it = 0;
  while ((mask & want) != want) {
    mask = __ballot_sync(~0u, ld_relaxed(flags + lane) == epoch);
    spin_guard(++it);
  }
}

__global__ void __cluster_dims__(2, 1, 1) __launch_bounds__(384, 1) mega_kernel(const __grid_constant__ Params p) {
  extern __shared__ __align__(1024) uint8_t smem_raw[];
  uint32_t sb = smem_u32(smem_raw);
  asm volatile("" : "+r"(sb));
  const int tid = threadIdx.x, lane = tid & 31, warp = __shfl_sync(~0u, tid >> 5, 0), wg = warp >> 2;
  const int b = blockIdx.x, m = b >> 3, n = b & 7, rank = b & 1;

  if (wg == 2) {
    if (tid == 256) {
      TL(0);
      spin_guard((sb & 1023) ? ~0u : 0u);
      for (int s = 0; s < 8; s++) { mbar_init(sb + B_FULL + 8 * s, 1); mbar_init(sb + B_EMPTY + 8 * s, 4); }
      mbar_init(sb + B_SCR, 4); mbar_init(sb + B_WPHI, 1); mbar_init(sb + B_VEC, 64); mbar_init(sb + B_UT, 64); mbar_init(sb + B_GS1, 8);
      mbar_init(sb + B_KV, 8); mbar_init(sb + B_T0, 2); mbar_init(sb + B_T1, 2);
      asm volatile("fence.mbarrier_init.release.cluster;" ::: "memory");
    }
    if (tid == 288) { prefetch_tmap(&p.tm_x); prefetch_tmap(&p.tm_wqkv); prefetch_tmap(&p.tm_wphi); }
    __syncwarp();
    cluster_arrive();
    const uint32_t epoch = ld_relaxed(&g_epoch) + 1;
    reg_dealloc<56>();
    cluster_wait();
    if (warp == 8) {
      if (lane == 0) {
        prod_range<J_KV, 0, 16, 6, false>(sb, [&](int i, uint32_t a, uint32_t bar, int need) {
          if (need >= 0) wait_empty(sb, need);
          mbar_expect_tx(bar, 49152);
          tma_load_3d(a + 16384, &p.tm_wqkv, bar, 0, i * 64, 16 + 2 * n);
          tma_load_3d(a + 32768, &p.tm_wqkv, bar, 0, i * 64, 32 + 2 * n);
          if (i == 3) { mbar_expect_tx(sb + B_WPHI, 8192); tma_load_2d(sb + SM_WPHI, &p.tm_wphi, sb + B_WPHI, 0, n * 128); }
        });
        prod_range<J_Q, 0, 16, 4, false>(sb, [&](int i, uint32_t a, uint32_t bar, int need) {
          wait_empty(sb, need); mbar_expect_tx(bar, 32768); tma_load_3d(a + 16384, &p.tm_wqkv, bar, 0, i * 64, 2 * n);
        });
        const uint32_t peer = mapa(sb, rank ^ 1);
        auto wo = [&](int i, uint32_t a, uint32_t bar, int need) {
          wait_empty(sb, need); mbar_expect_tx(bar, (i & 13) ? 32768 : 16384); tma_load_3d(a + 16384, &p.tm_wo, bar, 0, own_chunk(i, n) * 64, 2 * n);
        };
        prod_range<J_WO, 0, 5, 4, false>(sb, wo);
        mbar_wait(sb + B_T0, 0);
        bulk_store(g_o + (size_t)(m * 16 + 2 * n) * 16384, sb + OFF<J_WO>, 16384); bulk_commit();
        bulk_copy_peer(peer + OFF<J_WO + 1>, sb + OFF<J_WO>, 16384, peer + B_FULL + 8 * ((J_WO + 1) & 7));
        bulk_wait0(); st_relaxed(&g_oflag[m * 32 + 2 * n], epoch);
        TL(40);
        mbar_wait(sb + B_T1, 0);
        bulk_store(g_o + (size_t)(m * 16 + 2 * n + 1) * 16384, sb + OFF<J_WO + 2>, 16384); bulk_commit();
        bulk_copy_peer(peer + OFF<J_WO + 3>, sb + OFF<J_WO + 2>, 16384, peer + B_FULL + 8 * ((J_WO + 3) & 7));
        mbar_wait(sb + B_SCR, 0);
        prod_range<J_WO, 5, 6, 4, false>(sb, wo);
        bulk_wait0(); st_relaxed(&g_oflag[m * 32 + 2 * n + 1], epoch);
        TL(41);
        prod_range<J_WO, 6, 16, 4, false>(sb, wo);
        auto f1a = [&](int i, uint32_t a, uint32_t bar, int need) {
          wait_empty(sb, need); mbar_expect_tx(bar, (i & 13) ? 32768 : 16384); tma_load_3d(a + 16384, &p.tm_w1a, bar, 0, own_chunk(i, n) * 64, 2 * n);
        };
        prod_range<J_F1A, 0, 6, 4, false>(sb, f1a);
        mbar_wait(sb + B_T0, 1);
        bulk_store(g_x1g + (size_t)(m * 16 + 2 * n) * 16384, sb + OFF<J_F1A>, 16384); bulk_commit();
        bulk_copy_peer(peer + OFF<J_F1A + 1>, sb + OFF<J_F1A>, 16384, peer + B_FULL + 8 * ((J_F1A + 1) & 7));
        mbar_wait(sb + B_T1, 1);
        bulk_store(g_x1g + (size_t)(m * 16 + 2 * n + 1) * 16384, sb + OFF<J_F1A + 2>, 16384); bulk_commit();
        bulk_copy_peer(peer + OFF<J_F1A + 3>, sb + OFF<J_F1A + 2>, 16384, peer + B_FULL + 8 * ((J_F1A + 3) & 7));
        bulk_wait1(); st_relaxed(&g_xflag[m * 32 + 2 * n], epoch);
        bulk_wait0(); st_relaxed(&g_xflag[m * 32 + 2 * n + 1], epoch);
        TL(42);
        prod_range<J_F1A, 6, 16, 4, false>(sb, f1a);
        prod_range<J_F1B, 0, 16, 4, false>(sb, [&](int i, uint32_t a, uint32_t bar, int need) {
          wait_empty(sb, need); mbar_expect_tx(bar, 32768); tma_load_3d(a + 16384, &p.tm_w1a, bar, 0, i * 64, 16 + 2 * n);
        });
        prod_range<J_F1C, 0, 16, 5, false>(sb, [&](int i, uint32_t a, uint32_t bar, int need) {
          wait_empty(sb, need); mbar_expect_tx(bar, 40960); tma_load_3d(a + 16384, &p.tm_w1c, bar, 0, i * 64, 32 + 3 * n);
        });
        prod_range<J_F2, 0, 56, 4, false>(sb, [&](int i, uint32_t a, uint32_t bar, int need) {
          wait_empty(sb, need); mbar_expect_tx(bar, 32768); tma_load_3d(a + 16384, &p.tm_w2, bar, 0, i * 64, 2 * n);
        });
      }
    } else if (warp == 9) {
      const uint32_t ho = rank * 8192;
      prod_range<J_KV, 0, 16, 6, false>(sb, [&](int i, uint32_t a, uint32_t bar, int need) {
        if (need >= 0) wait_empty(sb, need);
        if (lane == 0) tma_load_2d_mc(a + ho, &p.tm_x, bar, i * 64, m * 128 + rank * 64, 3);
      });
      uint32_t mask = 0;
      prod_range<J_Q, 0, 16, 4, false>(sb, [&](int i, uint32_t a, uint32_t bar, int need) {
        poll_flags(g_hflag + (m * 2 + rank) * 32, lane, epoch, 0xFu << ((i >> 1) * 4), mask);
        wait_empty(sb, need);
        if (lane == 0) bulk_load_mc(a + ho, g_h + (size_t)(m * 16 + i) * 16384 + ho, 8192, bar);
      });
      const uint32_t pm = 5u << ((n & 6) * 2);
      mask = 0;
      prod_range<J_WO, 4, 16, 4, true>(sb, [&](int i, uint32_t a, uint32_t bar, int need) {
        int ch = own_chunk(i, n);
        poll_flags(g_oflag + m * 32, lane, epoch, (1u << ch) | (i >= 6 ? pm : 0u) | (i >= 8 ? pm * 2 : 0u), mask);
        wait_empty(sb, need);
        if (i == 5) mbar_wait(sb + B_SCR, 0);
        if (lane == 0) bulk_load_mc(a + ho, g_o + (size_t)(m * 16 + ch) * 16384 + ho, 8192, bar);
      });
      mask = 0;
      prod_range<J_F1A, 4, 16, 4, true>(sb, [&](int i, uint32_t a, uint32_t bar, int need) {
        int ch = own_chunk(i, n);
        poll_flags(g_xflag + m * 32, lane, epoch, (1u << ch) | (i >= 6 ? pm : 0u) | (i >= 8 ? pm * 2 : 0u), mask);
        wait_empty(sb, need);
        if (lane == 0) bulk_load_mc(a + ho, g_x1g + (size_t)(m * 16 + ch) * 16384 + ho, 8192, bar);
      });
      auto f1 = [&](int i, uint32_t a, uint32_t bar, int need) {
        wait_empty(sb, need);
        if (lane == 0) bulk_load_mc(a + ho, g_x1g + (size_t)(m * 16 + i) * 16384 + ho, 8192, bar);
      };
      prod_range<J_F1B, 0, 16, 4, false>(sb, f1);
      prod_range<J_F1C, 0, 16, 5, false>(sb, f1);
      const uint32_t* hf = g_hidflag + (m * 2 + rank) * 32;
      mask = 0;
      prod_range<J_F2, 0, 56, 4, false>(sb, [&](int i, uint32_t a, uint32_t bar, int need) {
        if (i == 16 || i == 32) { mask = 0; hf += 1024; }
        poll_flags(hf, lane, epoch, 0xFu << ((i < 32 ? (i & 15) >> 1 : (i - 32) / 3) * 4), mask);
        wait_empty(sb, need);
        if (lane == 0) bulk_load_mc(a + ho, g_hid + (size_t)(m * 56 + i) * 16384 + ho, 8192, bar);
      });
    } else {
      const int ht = tid - 320;
      for (int i = ht; i < 160; i += 64) g_kvacc[(epoch + 1) & 1][b * 160 + i] = make_float4(0.f, 0.f, 0.f, 0.f);
      for (int i = ht; i < 512; i += 64) {
        uint32_t cv = ld_nc1(p.c + 2 * i);
        sts2(sb + SM_GS2 + i * 8, pack_bf16(silu_bf(bf_lo(cv)), 0.f), pack_bf16(silu_bf(bf_hi(cv)), 0.f));
      }
      mbar_wait(sb + B_GS1, 0);
      if (ht < 8) bulk_prefetch(p.wqkv + (size_t)(b * 8 + ht) * 3072, 6144);
      else if (ht < 16) bulk_prefetch(p.wmod + (size_t)(b * 8 + ht - 8) * 6144 + 2048, 8192);
      __syncwarp();
      if (ht == 32) bulk_prefetch(p.wo + (size_t)b * 8192, 16384);
      else if (ht >= 40 && ht < 48) bulk_prefetch(p.w1 + (size_t)(b * 8 + ht - 40) * FF, FF * 2);
      bar_sync(4, 64);
      float o0, o1;
      gemv32<false>(p.wmod + 2048 + b * 32, 6144, sb + SM_GS2, sb + SM_RED, ht, o0, o1);
      {
        float nb = __shfl_down_sync(~0u, o0, 1);
        if (ht < 32 && !(ht & 1)) st_vol2(&g_modpk[1024 + b * 16 + (ht >> 1)], pack_bf16(o0, nb), epoch);
      }
      if (ht < 8) bulk_prefetch(p.w2 + (size_t)(b * 8 + ht) * FF, FF * 2);
      if (ht == 0) TL(48);
      bar_sync(4, 64);
      for (int i = ht; i < 256; i += 64) {
        uint4 s, cc;
        poll4x2(&g_modpk[1536 + 2 * i], &g_modpk[2048 + 2 * i], epoch, s, cc);
        sts4(sb + SM_GS2 + i * 16, pack_bf16(1.f + bf_lo(cc.x), bf_lo(s.x)), pack_bf16(1.f + bf_hi(cc.x), bf_hi(s.x)),
             pack_bf16(1.f + bf_lo(cc.z), bf_lo(s.z)), pack_bf16(1.f + bf_hi(cc.z), bf_hi(s.z)));
      }
      {
        uint2 ga = poll2(&g_modpk[1024 + n * 64 + ht], epoch), cb = poll2(&g_modpk[2048 + n * 64 + ht], epoch), gb = poll2(&g_modpk[2560 + n * 64 + ht], epoch);
        uint32_t b2 = ld_nc1(p.b2 + n * 128 + 2 * ht);
        sts4(sb + SM_VEC + ht * 16, __float_as_uint(bf_lo(ga.x)), __float_as_uint(bf_hi(ga.x)), pack_bf16(1.f + bf_lo(cb.x), 1.f + bf_hi(cb.x)), 0u);
        sts4(sb + SM_VEC + 1024 + ht * 16, __float_as_uint(bf_lo(gb.x)), __float_as_uint(bf_lo(b2)), __float_as_uint(bf_hi(gb.x)), __float_as_uint(bf_hi(b2)));
      }
      mbar_arrive(sb + B_VEC);
      if (ht == 0) TL(49);
      if (ht == 0) {
        mbar_wait(sb + B_KV, 0);
        TL(52);
        __threadfence();
        st_relaxed(&g_kvflag[n * 32 + m], epoch);
        TL(53);
      }
      bar_sync(4, 64);
      if (b < 112) {
        gemv32<true>(p.w1 + b * 32, FF, sb + SM_GS2, sb + SM_RED, ht, o0, o1);
        if (ht < 32) st_vol4(&g_utpk[b * 32 + ht], __float_as_uint(o0), epoch, __float_as_uint(o1 + __bfloat162float(p.b1[b * 32 + ht])), epoch);
      }
      if (ht == 0) TL(50);
      mbar_wait(sb + B_SCR, 0);
      if (ht == 0) { uint32_t t = atomicInc(&g_done, 127); if (t == 127) g_epoch = epoch; }
      for (int i = ht; i < 448; i += 64) {
        int col = i < 128 ? n * 128 + i : i < 256 ? 1024 + n * 128 + (i - 128) : 2048 + n * 192 + (i - 256);
        uint4 v = poll4(&g_utpk[col], epoch);
        sts2(sb + SM_WPHI + i * 8, v.x, v.z);
      }
      mbar_arrive(sb + B_UT);
      if (ht == 0) TL(51);
    }
  } else {
    const int q = lane & 3;
    const int r0 = m * 128 + wg * 64 + (warp & 3) * 16 + (lane >> 2);
    Ctx c;
    float rs0, nm0, rs1, nm1;
    {
      uint4 wv[8], xv[2][4];
      uint16_t cv[8];
      const bf16* wp = p.wmod + (size_t)(tid >> 1) * 6144 + b * 16 + (tid & 1) * 8;
#pragma unroll
      for (int i = 0; i < 8; i++) wv[i] = ld_nc4p(wp + (size_t)i * 128 * 6144);
#pragma unroll
      for (int i = 0; i < 8; i++) asm volatile("ld.global.nc.u16 %0, [%1];" : "=h"(cv[i]) : "l"(p.c + (tid >> 1) + i * 128));
      const uint32_t epoch = ld_relaxed(&g_epoch) + 1;
      const int row0 = m * 128 + n * 16 + warp * 2;
#pragma unroll
      for (int r = 0; r < 2; r++)
#pragma unroll
        for (int i = 0; i < 4; i++) xv[r][i] = ld_nc4(p.x + (size_t)(row0 + r) * DM + i * 256 + lane * 8);
      cluster_arrive();
      reg_alloc<224>();
      c.sb = sb; c.wg = wg; c.tid = tid & 127; c.lane = lane; c.w4 = warp & 3; c.epoch = epoch;
      c.ebase = mapa(sb + B_EMPTY, tid & 1); c.stg = sb + SM_STG + warp * 2048;
      c.srow = (lane & 15) * 128 + (((lane >> 4) ^ (lane & 7)) << 4);
      float a[8];
#pragma unroll
      for (int e = 0; e < 8; e++) a[e] = 0.f;
#pragma unroll
      for (int i = 0; i < 8; i++) {
        float cf = silu_bf(bf_lo(cv[i]));
        uint32_t vv[4] = {wv[i].x, wv[i].y, wv[i].z, wv[i].w};
#pragma unroll
        for (int e = 0; e < 4; e++) { a[2 * e] = fmaf(cf, bf_lo(vv[e]), a[2 * e]); a[2 * e + 1] = fmaf(cf, bf_hi(vv[e]), a[2 * e + 1]); }
      }
#pragma unroll
      for (int e = 0; e < 4; e++) { bool up = lane & 8; float s = up ? a[e] : a[e + 4], k = up ? a[e + 4] : a[e]; a[e] = k + __shfl_xor_sync(~0u, s, 8); }
#pragma unroll
      for (int e = 0; e < 2; e++) { bool up = lane & 4; float s = up ? a[e] : a[e + 2], k = up ? a[e + 2] : a[e]; a[e] = k + __shfl_xor_sync(~0u, s, 4); }
      { bool up = lane & 2; float s = up ? a[0] : a[1], k = up ? a[1] : a[0]; a[0] = k + __shfl_xor_sync(~0u, s, 2); }
      a[0] += __shfl_xor_sync(~0u, a[0], 16);
      if (lane < 16) sts1(sb + SM_RED + warp * 64 + ((lane & 1) * 8 + (lane >> 1)) * 4, __float_as_uint(a[0]));
      bar_sync(3, 256);
      if (tid < 8) {
        float s0 = 0.f, s1 = 0.f;
#pragma unroll
        for (int w = 0; w < 8; w++) { uint2 v = lds2(sb + SM_RED + w * 64 + tid * 8); s0 += __uint_as_float(v.x); s1 += __uint_as_float(v.y); }
        st_vol2(&g_modpk[b * 8 + tid], pack_bf16(s0, s1), epoch);
      }
      if (tid == 0) TL(1);
      float s[2], v2[2];
#pragma unroll
      for (int r = 0; r < 2; r++) {
        s[r] = 0.f;
#pragma unroll
        for (int i = 0; i < 4; i++) { uint32_t vv[4] = {xv[r][i].x, xv[r][i].y, xv[r][i].z, xv[r][i].w};
#pragma unroll
          for (int e = 0; e < 4; e++) s[r] += bf_lo(vv[e]) + bf_hi(vv[e]); }
      }
#pragma unroll
      for (int o = 1; o < 32; o <<= 1) { s[0] += __shfl_xor_sync(~0u, s[0], o); s[1] += __shfl_xor_sync(~0u, s[1], o); }
#pragma unroll
      for (int r = 0; r < 2; r++) {
        s[r] *= (1.f / DM); v2[r] = 0.f;
#pragma unroll
        for (int i = 0; i < 4; i++) { uint32_t vv[4] = {xv[r][i].x, xv[r][i].y, xv[r][i].z, xv[r][i].w};
#pragma unroll
          for (int e = 0; e < 4; e++) { float d0 = bf_lo(vv[e]) - s[r], d1 = bf_hi(vv[e]) - s[r]; v2[r] = fmaf(d0, d0, v2[r]); v2[r] = fmaf(d1, d1, v2[r]); } }
      }
#pragma unroll
      for (int o = 1; o < 32; o <<= 1) { v2[0] += __shfl_xor_sync(~0u, v2[0], o); v2[1] += __shfl_xor_sync(~0u, v2[1], o); }
      if (lane < 2) {
        float rs = rsqrtf((lane ? v2[1] : v2[0]) * (1.f / DM) + 1e-5f);
        st_vol4(&g_st1pk[row0 + lane], __float_as_uint(rs), epoch, __float_as_uint(-(lane ? s[1] : s[0]) * rs), epoch);
      }
      if (tid == 0) TL(19);
      cluster_wait();
      if (lane == 0) mbar_arrive(sb + B_GS1);
      {
        uint4 sv, cc;
        poll4x2(&g_modpk[2 * tid], &g_modpk[512 + 2 * tid], epoch, sv, cc);
        uint32_t ad = sb + SM_GS1 + (tid >> 2) * 64 + (tid & 1) * 32 + ((tid >> 1) & 1) * 4;
        sts1(ad, pack_bf16(1.f + bf_lo(cc.x), 1.f + bf_hi(cc.x))); sts1(ad + 8, sv.x);
        sts1(ad + 16, pack_bf16(1.f + bf_lo(cc.z), 1.f + bf_hi(cc.z))); sts1(ad + 24, sv.z);
        poll4x2(&g_st1pk[r0], &g_st1pk[r0 + 8], epoch, sv, cc);
        rs0 = __uint_as_float(sv.x); nm0 = __uint_as_float(sv.z); rs1 = __uint_as_float(cc.x); nm1 = __uint_as_float(cc.z);
      }
      bar_sync(3, 256);
      if (tid == 0) TL(2);
    }
    const uint32_t epoch = c.epoch;
    const uint32_t wrow = wg * 8192 + c.w4 * 2048;
    Pipe pp;
    float accq[64];
    uint32_t kp[32], vp[32];
    {
      float acc[128];
      uint32_t A0[16], A1[16];
      pp.g = 0; pp.a = sb;
      auto kv_step = [&](uint32_t (&A)[16], auto first) {
        wait_full(c, pp);
#pragma unroll
        for (int k = 0; k < 4; k++) {
          ldmatrix_x4(stm_addr(c, pp.a + wrow, 2 * k), A[4 * k], A[4 * k + 1], A[4 * k + 2], A[4 * k + 3]);
          uint4 gs = lds4(sb + SM_GS1 + (pp.g * 4 + k) * 64 + q * 16);
          A[4 * k] = hfma2(pack_bf16(fmaf(bf_lo(A[4 * k]), rs0, nm0), fmaf(bf_hi(A[4 * k]), rs0, nm0)), gs.x, gs.z);
          A[4 * k + 1] = hfma2(pack_bf16(fmaf(bf_lo(A[4 * k + 1]), rs1, nm1), fmaf(bf_hi(A[4 * k + 1]), rs1, nm1)), gs.x, gs.z);
          A[4 * k + 2] = hfma2(pack_bf16(fmaf(bf_lo(A[4 * k + 2]), rs0, nm0), fmaf(bf_hi(A[4 * k + 2]), rs0, nm0)), gs.y, gs.w);
          A[4 * k + 3] = hfma2(pack_bf16(fmaf(bf_lo(A[4 * k + 3]), rs1, nm1), fmaf(bf_hi(A[4 * k + 3]), rs1, nm1)), gs.y, gs.w);
        }
        uint32_t db = desc_lo(pp.a + 16384, 8192);
        wgmma_fence();
        if constexpr (decltype(first)::value) wgmma_rsz_n256<1, H128>(acc, A[0], A[1], A[2], A[3], db);
        else wgmma_rs_n256<1, H128>(acc, A[0], A[1], A[2], A[3], db);
#pragma unroll
        for (int k = 1; k < 4; k++) wgmma_rs_n256<1, H128>(acc, A[4 * k], A[4 * k + 1], A[4 * k + 2], A[4 * k + 3], db + k * 128);
        wgmma_commit();
        if ((int)(pp.g >> 1) == n) {
          stg_acquire(c);
#pragma unroll
          for (int k = 0; k < 4; k++) stmatrix_x4(stm_addr(c, c.stg, 2 * k), A[4 * k], A[4 * k + 1], A[4 * k + 2], A[4 * k + 3]);
          stg_store(c, g_h + (size_t)(m * 16 + pp.g) * 16384 + wrow);
        }
        if ((int)pp.g == 2 * n + 2) warp_publish(c, &g_hflag[(m * 2 + wg) * 32 + n * 4 + c.w4]);
        wgmma_wait<1>();
        if (!decltype(first)::value) release_stage(c, pp.g - 1);
        pp.g++; pp.a = next_slot<6, false>(pp.a, sb);
      };
      kv_step(A0, std::true_type{});
      if (tid == 0) TL(3);
#pragma unroll 1
      for (int i = 0; i < 7; i++) { kv_step(A1, std::false_type{}); kv_step(A0, std::false_type{}); }
      kv_step(A1, std::false_type{});
      pp.a = sb + OFF<J_Q>;
      wgmma_wait<0>();
      step<128, true, true, true>(c, pp, accq);
      fence_regs(acc);
      if (tid == 0) TL(4);
      if (n == 7) warp_publish(c, &g_hflag[(m * 2 + wg) * 32 + n * 4 + c.w4]);
#pragma unroll
      for (int i = 0; i < 32; i++) { kp[i] = pack_bf16(acc[2 * i], acc[2 * i + 1]); vp[i] = pack_bf16(acc[64 + 2 * i], acc[64 + 2 * i + 1]); }
    }
    {
      const uint32_t phi_t = sb + SM_SCR + wg * 16384, v_t = phi_t + 8192;
      wait_empty(sb, 13);
      mbar_wait(sb + B_WPHI, 0);
      if (lane < 16) sts4(v_t + c.w4 * 2048 + lane * 128 + ((4 ^ (lane & 7)) << 4), 0x3f803f80u, 0x3f803f80u, 0x3f803f80u, 0x3f803f80u);
      if (wg) step<128, false, true, true>(c, pp, accq);
#pragma unroll
      for (int hh = 0; hh < 4; hh++) {
        float pk[16];
        wait_full(c, pp);
        wgmma_fence();
        phi_mma(pk, kp + hh * 8, sb + SM_WPHI + hh * 2048);
        wgmma_commit();
        mma4<128, false>(c, accq, pp);
        wgmma_commit();
        wgmma_wait<1>();
        fence_regs(pk);
        release_stage(c, pp.g - 1);
        pp.g++; pp.a = next_slot<4, true>(pp.a, sb);
        uint32_t ph[16];
        dual_softmax(pk, ph);
        if (hh > 0) bar_sync(1 + wg, 128);
#pragma unroll
        for (int jj = 0; jj < 4; jj++) stmatrix_x4(stm_addr(c, phi_t + c.w4 * 2048, jj * 2), ph[4 * jj], ph[4 * jj + 1], ph[4 * jj + 2], ph[4 * jj + 3]);
#pragma unroll
        for (int jj = 0; jj < 2; jj++) stmatrix_x4(stm_addr(c, v_t + c.w4 * 2048, jj * 2), vp[hh * 8 + 4 * jj], vp[hh * 8 + 4 * jj + 1], vp[hh * 8 + 4 * jj + 2], vp[hh * 8 + 4 * jj + 3]);
        fence_async_smem();
        bar_sync(1 + wg, 128);
        float kv[20];
        wait_full(c, pp);
        wgmma_fence();
        wgmma_ssz_n40<1, 1, H128>(kv, desc_lo(phi_t, 8192), desc_lo(v_t, 8192));
#pragma unroll
        for (int s = 1; s < 4; s++)
          wgmma_ss_n40<1, 1, H128>(kv, desc_lo(phi_t + s * 2048, 8192), desc_lo(v_t + s * 2048, 8192));
        wgmma_commit();
        mma4<128, false>(c, accq, pp);
        wgmma_commit();
        wgmma_wait<1>();
        fence_regs(kv);
        release_stage(c, pp.g - 1);
        pp.g++; pp.a = next_slot<4, true>(pp.a, sb);
        float4* dst = &g_kvacc[epoch & 1][(n * 4 + hh) * 640 + c.tid];
#pragma unroll
        for (int j = 0; j < 5; j++) red_add4(dst + j * 128, kv[4 * j], kv[4 * j + 1], kv[4 * j + 2], kv[4 * j + 3]);
      }
      __syncwarp();
      if (lane == 0) mbar_arrive(sb + B_KV);
      if (tid == 0) TL(5);
#pragma unroll 1
      while (pp.g < J_WO) step<128, false, true, true>(c, pp, accq);
    }
    float accw[64];
    {
      {
        uint32_t mask = 0;
        poll_flags(g_kvflag + n * 32, lane, epoch, 0xFFFFu, mask);
      }
      if (tid == 0) TL(7);
      uint4 v[10];
      {
        const float4* src = &g_kvacc[epoch & 1][(n * 4 + wg * 2) * 640 + c.tid];
#pragma unroll
        for (int i = 0; i < 10; i++) v[i] = ld_vol4(src + i * 128);
      }
      wgmma_wait<0>();
      fence_regs(accq);
      release_stage(c, J_WO - 1);
      if (tid == 0) TL(6);
      float pq[4][16];
      {
        uint32_t qp[32];
#pragma unroll
        for (int i = 0; i < 32; i++) qp[i] = pack_bf16(accq[2 * i], accq[2 * i + 1]);
        wgmma_fence();
#pragma unroll
        for (int hh = 0; hh < 4; hh++) phi_mma(pq[hh], qp + hh * 8, sb + SM_WPHI + hh * 2048);
        wgmma_commit();
        int f = c.w4 * 16 + (lane >> 2);
#pragma unroll
        for (int i = 0; i < 10; i++) {
          uint32_t a = sb + SM_SCR + (wg * 2 + i / 5) * 8192 + f * 128 + (((i % 5) ^ (f & 7)) << 4) + q * 4;
          sts1(a, pack_bf16(__uint_as_float(v[i].x), __uint_as_float(v[i].y)));
          sts1(a + 1024, pack_bf16(__uint_as_float(v[i].z), __uint_as_float(v[i].w)));
        }
        fence_async_smem();
        wgmma_wait<0>();
#pragma unroll
        for (int hh = 0; hh < 4; hh++) fence_regs(pq[hh]);
      }
      wait_empty(sb, NEED<J_WO + 2>);
      pp.a = sb + OFF<J_WO>;
      auto num_mma = [&](float (&nd)[20], const uint32_t (&ph)[16], int hh) {
        wgmma_rsz_n40<1, H128>(nd, ph[0], ph[1], ph[2], ph[3], desc_lo(sb + SM_SCR + hh * 8192, 8192));
#pragma unroll
        for (int s = 1; s < 4; s++)
          wgmma_rs_n40<1, H128>(nd, ph[4 * s], ph[4 * s + 1], ph[4 * s + 2], ph[4 * s + 3], desc_lo(sb + SM_SCR + hh * 8192 + s * 2048, 8192));
        wgmma_commit();
      };
      auto o_out = [&](float (&nd)[20], int hh) {
        fence_regs(nd);
        float i0 = rcp(nd[16] + 1e-6f), i1 = rcp(nd[18] + 1e-6f);
#pragma unroll
        for (int jj = 0; jj < 2; jj++)
          stmatrix_x4(stm_addr(c, sb + ((hh & 2) ? OFF<J_WO + 2> : OFF<J_WO>) + wrow, (hh & 1) * 4 + jj * 2), pack_bf16(nd[8 * jj] * i0, nd[8 * jj + 1] * i0),
                      pack_bf16(nd[8 * jj + 2] * i1, nd[8 * jj + 3] * i1), pack_bf16(nd[8 * jj + 4] * i0, nd[8 * jj + 5] * i0), pack_bf16(nd[8 * jj + 6] * i1, nd[8 * jj + 7] * i1));
      };
      uint32_t ph0[16], ph1[16];
      float nd0[20], nd1[20];
      dual_softmax(pq[0], ph0);
      bar_sync(3, 256);
      wgmma_fence(); num_mma(nd0, ph0, 0);
      dual_softmax(pq[1], ph1);
      wgmma_fence(); num_mma(nd1, ph1, 1);
      wgmma_wait<1>();
      o_out(nd0, 0);
      wgmma_wait<0>();
      o_out(nd1, 1);
      fence_async_smem();
      bar_sync(1 + wg, 128);
      if (c.tid == 0) mbar_arrive(sb + B_T0);
      if (tid == 0) TL(20);
      wait_full(c, pp);
      wgmma_fence(); mma4<128, true>(c, accw, pp); wgmma_commit();
      pp.g++; pp.a = next_slot<4, false>(pp.a, sb);
      dual_softmax(pq[2], ph0);
      wgmma_fence(); num_mma(nd0, ph0, 2);
      wait_full(c, pp);
      wgmma_fence(); mma4<128, false>(c, accw, pp); wgmma_commit();
      pp.g++; pp.a = next_slot<4, false>(pp.a, sb);
      dual_softmax(pq[3], ph1);
      wgmma_fence(); num_mma(nd1, ph1, 3);
      wgmma_wait<2>();
      release_stage(c, J_WO);
      o_out(nd0, 2);
      wgmma_wait<0>();
      release_stage(c, J_WO + 1);
      o_out(nd1, 3);
      fence_async_smem();
      bar_sync(1 + wg, 128);
      if (c.tid == 0) mbar_arrive(sb + B_T1);
      if (c.tid < 2) mbar_arrive_cl(c.ebase + (B_SCR - B_EMPTY));
      if (tid == 0) TL(8);
    }
    float acca[64];
    {
      step<128, false, false, false>(c, pp, accw);
      uint32_t xr[32];
#pragma unroll
      for (int j = 0; j < 16; j++) {
        xr[2 * j] = ld_nc1(p.x + (size_t)r0 * DM + n * 128 + j * 8 + q * 2);
        xr[2 * j + 1] = ld_nc1(p.x + (size_t)(r0 + 8) * DM + n * 128 + j * 8 + q * 2);
      }
#pragma unroll 1
      while (pp.g < J_F1A) step<128, false, false, true>(c, pp, accw);
      mbar_wait(sb + B_VEC, 0);
      wait_empty(sb, NEED<J_F1A + 2>);
      wgmma_wait<0>();
      fence_regs(accw);
      release_stage(c, J_F1A - 1);
      if (tid == 0) TL(9);
      pp.a = sb + OFF<J_F1A>;
#pragma unroll
      for (int pc = 0; pc < 2; pc++) {
#pragma unroll
        for (int jj = 0; jj < 4; jj++) {
          uint32_t r[4];
#pragma unroll
          for (int e = 0; e < 2; e++) {
            int j = pc * 8 + jj * 2 + e;
            uint4 gv = lds4(sb + SM_VEC + (j * 4 + q) * 16);
            float ga0 = __uint_as_float(gv.x), ga1 = __uint_as_float(gv.y);
            xr[2 * j] = pack_bf16(fmaf(ga0, accw[4 * j], bf_lo(xr[2 * j])), fmaf(ga1, accw[4 * j + 1], bf_hi(xr[2 * j])));
            xr[2 * j + 1] = pack_bf16(fmaf(ga0, accw[4 * j + 2], bf_lo(xr[2 * j + 1])), fmaf(ga1, accw[4 * j + 3], bf_hi(xr[2 * j + 1])));
            r[2 * e] = hmul2(xr[2 * j], gv.z); r[2 * e + 1] = hmul2(xr[2 * j + 1], gv.z);
          }
          stmatrix_x4(stm_addr(c, sb + (pc ? OFF<J_F1A + 2> : OFF<J_F1A>) + wrow, jj * 2), r[0], r[1], r[2], r[3]);
        }
        fence_async_smem();
        bar_sync(1 + wg, 128);
        if (c.tid == 0) mbar_arrive(sb + (pc ? B_T1 : B_T0));
        if (pc == 0) {
          wait_full(c, pp);
          wgmma_fence(); mma4<128, true>(c, acca, pp); wgmma_commit();
          pp.g++; pp.a = next_slot<4, false>(pp.a, sb);
        }
      }
      if (tid == 0) TL(10);
      step<128, false, false, true>(c, pp, acca);
      float s0 = 0.f, s1 = 0.f;
#pragma unroll
      for (int j = 0; j < 16; j++) { s0 += bf_lo(xr[2 * j]) + bf_hi(xr[2 * j]); s1 += bf_lo(xr[2 * j + 1]) + bf_hi(xr[2 * j + 1]); }
      s0 += __shfl_xor_sync(~0u, s0, 1); s1 += __shfl_xor_sync(~0u, s1, 1);
      s0 += __shfl_xor_sync(~0u, s0, 2); s1 += __shfl_xor_sync(~0u, s1, 2);
      s0 *= (1.f / 128); s1 *= (1.f / 128);
      step<128, false, false, true>(c, pp, acca);
      float v0 = 0.f, v1 = 0.f;
#pragma unroll
      for (int j = 0; j < 16; j++) {
        float d0 = bf_lo(xr[2 * j]) - s0, d1 = bf_hi(xr[2 * j]) - s0, d2 = bf_lo(xr[2 * j + 1]) - s1, d3 = bf_hi(xr[2 * j + 1]) - s1;
        v0 = fmaf(d0, d0, v0); v0 = fmaf(d1, d1, v0); v1 = fmaf(d2, d2, v1); v1 = fmaf(d3, d3, v1);
      }
      v0 += __shfl_xor_sync(~0u, v0, 1); v1 += __shfl_xor_sync(~0u, v1, 1);
      v0 += __shfl_xor_sync(~0u, v0, 2); v1 += __shfl_xor_sync(~0u, v1, 2);
      if (q < 2) st_vol4(&g_st2pk[(r0 + q * 8) * 8 + n], __float_as_uint(q ? s1 : s0), epoch, __float_as_uint(q ? v1 : v0), epoch);
      step<128, false, false, true>(c, pp, acca);
#pragma unroll
      for (int i = 0; i < 8; i++) g_x1f[(b * 8 + i) * 256 + tid] = make_uint4(xr[4 * i], xr[4 * i + 1], xr[4 * i + 2], xr[4 * i + 3]);
    }
    RowStat rs;
    uint8_t* hid = g_hid + (size_t)m * 56 * 16384 + wrow;
    uint32_t* hflag = &g_hidflag[(m * 2 + wg) * 32 + n * 4 + c.w4];
#pragma unroll 1
    while (pp.g < J_F1B - 1) step<128, false, false, true>(c, pp, acca);
    {
      uint4 a0, a1, b0, b1;
      poll4x2(&g_st2pk[r0 * 8 + q * 2], &g_st2pk[r0 * 8 + q * 2 + 1], epoch, a0, a1);
      poll4x2(&g_st2pk[(r0 + 8) * 8 + q * 2], &g_st2pk[(r0 + 8) * 8 + q * 2 + 1], epoch, b0, b1);
      step<128, false, false, true>(c, pp, acca);
      float m0 = __uint_as_float(a0.x) + __uint_as_float(a1.x), m1 = __uint_as_float(b0.x) + __uint_as_float(b1.x);
      m0 += __shfl_xor_sync(~0u, m0, 1); m1 += __shfl_xor_sync(~0u, m1, 1);
      m0 += __shfl_xor_sync(~0u, m0, 2); m1 += __shfl_xor_sync(~0u, m1, 2);
      m0 *= 0.125f; m1 *= 0.125f;
      float d0 = __uint_as_float(a0.x) - m0, d1 = __uint_as_float(a1.x) - m0, d2 = __uint_as_float(b0.x) - m1, d3 = __uint_as_float(b1.x) - m1;
      float v0 = __uint_as_float(a0.z) + __uint_as_float(a1.z) + 128.f * (d0 * d0 + d1 * d1);
      float v1 = __uint_as_float(b0.z) + __uint_as_float(b1.z) + 128.f * (d2 * d2 + d3 * d3);
      v0 += __shfl_xor_sync(~0u, v0, 1); v1 += __shfl_xor_sync(~0u, v1, 1);
      v0 += __shfl_xor_sync(~0u, v0, 2); v1 += __shfl_xor_sync(~0u, v1, 2);
      rs.mu0 = m0; rs.mu1 = m1; rs.rs0 = rsqrtf(v0 * (1.f / DM) + 1e-5f); rs.rs1 = rsqrtf(v1 * (1.f / DM) + 1e-5f);
    }
    float accb[64];
    step<128, true, false, true>(c, pp, accb);
    fence_regs(acca);
    if (tid == 0) TL(11);
    mbar_wait(sb + B_UT, 0);
    ffn1_half<128, 0>(c, acca, 0, hid + 2 * n * 16384, rs);
    step<128, false, false, true>(c, pp, accb);
    ffn1_half<128, 1>(c, acca, 0, hid + 2 * n * 16384, rs);
    step<128, false, false, true>(c, pp, accb);
    ffn1_half<128, 2>(c, acca, 0, hid + 2 * n * 16384, rs);
    step<128, false, false, true>(c, pp, accb);
    ffn1_half<128, 3>(c, acca, 0, hid + 2 * n * 16384, rs);
#pragma unroll 1
    while (pp.g < J_F1C) { step<128, false, false, true>(c, pp, accb); if (pp.g == J_F1B + 8) warp_publish(c, hflag); }
    float accc[96];
    pp.a = sb + OFF<J_F1C>;
    step<192, true, false, true>(c, pp, accc);
    fence_regs(accb);
    if (tid == 0) TL(13);
    ffn1_half<128, 0>(c, accb, 128, hid + (16 + 2 * n) * 16384, rs);
    step<192, false, false, true>(c, pp, accc);
    ffn1_half<128, 1>(c, accb, 128, hid + (16 + 2 * n) * 16384, rs);
    step<192, false, false, true>(c, pp, accc);
    ffn1_half<128, 2>(c, accb, 128, hid + (16 + 2 * n) * 16384, rs);
    step<192, false, false, true>(c, pp, accc);
    ffn1_half<128, 3>(c, accb, 128, hid + (16 + 2 * n) * 16384, rs);
#pragma unroll 1
    while (pp.g < J_F2) { step<192, false, false, true>(c, pp, accc); if (pp.g == J_F1C + 8) warp_publish(c, hflag + 1024); }
    float acc[64];
    pp.a = sb + OFF<J_F2>;
    step<128, true, false, true>(c, pp, acc);
    fence_regs(accc);
    if (tid == 0) TL(15);
    ffn1_half<192, 0>(c, accc, 256, hid + (32 + 3 * n) * 16384, rs);
    step<128, false, false, true>(c, pp, acc);
    ffn1_half<192, 1>(c, accc, 256, hid + (32 + 3 * n) * 16384, rs);
    step<128, false, false, true>(c, pp, acc);
    ffn1_half<192, 2>(c, accc, 256, hid + (32 + 3 * n) * 16384, rs);
    step<128, false, false, true>(c, pp, acc);
    ffn1_half<192, 3>(c, accc, 256, hid + (32 + 3 * n) * 16384, rs);
    step<128, false, false, true>(c, pp, acc);
    ffn1_half<192, 4>(c, accc, 256, hid + (32 + 3 * n) * 16384, rs);
    step<128, false, false, true>(c, pp, acc);
    ffn1_half<192, 5>(c, accc, 256, hid + (32 + 3 * n) * 16384, rs);
#pragma unroll 1
    while (pp.g <= LAST_REL + 1) { step<128, false, false, true>(c, pp, acc); if (pp.g == J_F2 + 10) warp_publish(c, hflag + 2048); }
    uint32_t xr[32];
#pragma unroll
    for (int i = 0; i < 8; i++) { uint4 v = g_x1f[(b * 8 + i) * 256 + tid]; xr[4 * i] = v.x; xr[4 * i + 1] = v.y; xr[4 * i + 2] = v.z; xr[4 * i + 3] = v.w; }
#pragma unroll 1
    while (pp.g < NST) step<128, false, false, false>(c, pp, acc);
    wgmma_wait<0>();
    fence_regs(acc);
    if (tid == 0) TL(17);
#pragma unroll
    for (int pc = 0; pc < 2; pc++) {
      const uint32_t ob = sb + pc * 32768 + wrow;
#pragma unroll
      for (int jj = 0; jj < 4; jj++) {
        uint32_t r[4];
#pragma unroll
        for (int e = 0; e < 2; e++) {
          int j = pc * 8 + jj * 2 + e;
          uint4 gv = lds4(sb + SM_VEC + 1024 + (j * 4 + q) * 16);
          float gb0 = __uint_as_float(gv.x), b20 = __uint_as_float(gv.y), gb1 = __uint_as_float(gv.z), b21 = __uint_as_float(gv.w);
          r[2 * e] = pack_bf16(fmaf(gb0, acc[4 * j] + b20, bf_lo(xr[2 * j])), fmaf(gb1, acc[4 * j + 1] + b21, bf_hi(xr[2 * j])));
          r[2 * e + 1] = pack_bf16(fmaf(gb0, acc[4 * j + 2] + b20, bf_lo(xr[2 * j + 1])), fmaf(gb1, acc[4 * j + 3] + b21, bf_hi(xr[2 * j + 1])));
        }
        stmatrix_x4(stm_addr(c, ob, jj * 2), r[0], r[1], r[2], r[3]);
      }
      fence_async_smem();
      __syncwarp();
      if (lane == 0) { tma_store_2d(&p.tm_out, ob, n * 128 + pc * 64, m * 128 + wg * 64 + c.w4 * 16); bulk_commit(); }
    }
    if (lane == 0) bulk_wait_read0();
    if (tid == 0) TL(18);
  }
}

typedef CUresult (*PFN_encodeTiled)(CUtensorMap*, CUtensorMapDataType, cuuint32_t, void*, const cuuint64_t*, const cuuint64_t*, const cuuint32_t*,
                                    const cuuint32_t*, CUtensorMapInterleave, CUtensorMapSwizzle, CUtensorMapL2promotion, CUtensorMapFloatOOBfill);
static void map_2d(PFN_encodeTiled enc, CUtensorMap* m, const void* ptr, uint64_t rows, uint64_t cols, uint32_t brows, uint32_t bcols, CUtensorMapSwizzle sw) {
  cuuint64_t dims[2] = {cols, rows}; cuuint64_t strides[1] = {cols * 2}; cuuint32_t box[2] = {bcols, brows}; cuuint32_t es[2] = {1, 1};
  enc(m, CU_TENSOR_MAP_DATA_TYPE_BFLOAT16, 2, (void*)ptr, dims, strides, box, es, CU_TENSOR_MAP_INTERLEAVE_NONE, sw,
      CU_TENSOR_MAP_L2_PROMOTION_L2_256B, CU_TENSOR_MAP_FLOAT_OOB_FILL_NONE);
}
static void map_3d(PFN_encodeTiled enc, CUtensorMap* m, const void* ptr, uint64_t rows, uint64_t cols, uint32_t nchunks) {
  cuuint64_t dims[3] = {64, rows, cols / 64}; cuuint64_t strides[2] = {cols * 2, 128}; cuuint32_t box[3] = {64, 64, nchunks}; cuuint32_t es[3] = {1, 1, 1};
  enc(m, CU_TENSOR_MAP_DATA_TYPE_BFLOAT16, 3, (void*)ptr, dims, strides, box, es, CU_TENSOR_MAP_INTERLEAVE_NONE, CU_TENSOR_MAP_SWIZZLE_128B,
      CU_TENSOR_MAP_L2_PROMOTION_L2_256B, CU_TENSOR_MAP_FLOAT_OOB_FILL_NONE);
}

extern "C" void kernel_launch(void* const* d_in, const int* in_sizes, int n_in, void* d_out, int out_size) {
  void* fp = nullptr; cudaDriverEntryPointQueryResult qr;
  cudaGetDriverEntryPoint("cuTensorMapEncodeTiled", &fp, cudaEnableDefault, &qr);
  PFN_encodeTiled enc = (PFN_encodeTiled)fp;
  Params p;
  map_2d(enc, &p.tm_x, d_in[0], SEQ, DM, 64, 64, CU_TENSOR_MAP_SWIZZLE_128B);
  map_2d(enc, &p.tm_out, d_out, SEQ, DM, 16, 64, CU_TENSOR_MAP_SWIZZLE_128B);
  map_3d(enc, &p.tm_wqkv, d_in[1], DM, 3 * DM, 2);
  map_3d(enc, &p.tm_wo, d_in[3], DM, DM, 2);
  map_3d(enc, &p.tm_w1a, d_in[5], DM, FF, 2);
  map_3d(enc, &p.tm_w1c, d_in[5], DM, FF, 3);
  map_3d(enc, &p.tm_w2, d_in[7], FF, DM, 2);
  map_2d(enc, &p.tm_wphi, d_in[2], 1024, 32, 128, 32, CU_TENSOR_MAP_SWIZZLE_64B);
  p.x = (const bf16*)d_in[0]; p.wqkv = (const bf16*)d_in[1]; p.wo = (const bf16*)d_in[3]; p.w1 = (const bf16*)d_in[5]; p.w2 = (const bf16*)d_in[7];
  p.b1 = (const bf16*)d_in[6]; p.b2 = (const bf16*)d_in[8]; p.c = (const bf16*)d_in[9]; p.wmod = (const bf16*)d_in[10];
  cudaFuncSetAttribute(mega_kernel, cudaFuncAttributeMaxDynamicSharedMemorySize, SM_TOTAL);
  mega_kernel<<<128, 384, SM_TOTAL>>>(p);
}
```

```cpp
#include <cuda_runtime.h>
#include <cuda_bf16.h>
#include <cuda.h>
#include <stdint.h>
#include <type_traits>

typedef __nv_bfloat16 bf16;
#define SPIN_LIMIT (1u << 21)
constexpr int SEQ = 2048, DM = 1024, FF = 3584;

__device__ uint32_t g_epoch;
__device__ uint32_t g_done;
__device__ uint2 g_modpk[3072];
__device__ uint4 g_st1pk[SEQ];
__device__ uint4 g_st2pk[SEQ * 8];
__device__ uint4 g_utpk[FF];
__device__ __align__(1024) uint8_t g_act[16 * 104 * 16384];
__device__ uint4 g_x1f[128 * 8 * 256];
__device__ float4 g_kvacc[2][32 * 5 * 128];
__device__ __align__(128) uint32_t g_flag[16 * 10 * 32];
__device__ __align__(128) uint32_t g_kvflag[8 * 32];
#define TL(i) do { } while (0)

__device__ __forceinline__ uint32_t smem_u32(const void* p) { return (uint32_t)__cvta_generic_to_shared(p); }
__device__ __forceinline__ void mbar_init(uint32_t bar, uint32_t cnt) { asm volatile("mbarrier.init.shared::cta.b64 [%0], %1;" :: "r"(bar), "r"(cnt) : "memory"); }
__device__ __forceinline__ void mbar_expect_tx(uint32_t bar, uint32_t bytes) { asm volatile("mbarrier.arrive.expect_tx.shared::cta.b64 _, [%0], %1;" :: "r"(bar), "r"(bytes) : "memory"); }
__device__ __forceinline__ void mbar_arrive(uint32_t bar) { asm volatile("mbarrier.arrive.shared::cta.b64 _, [%0];" :: "r"(bar) : "memory"); }
__device__ __forceinline__ void mbar_arrive_cluster(uint32_t bar, uint32_t cta) {
  asm volatile("{\n.reg .b32 ra;\nmapa.shared::cluster.u32 ra, %0, %1;\nmbarrier.arrive.shared::cluster.b64 _, [ra];\n}\n" :: "r"(bar), "r"(cta) : "memory");
}
__device__ __forceinline__ bool mbar_try_wait(uint32_t bar, uint32_t parity) {
  uint32_t ok;
  asm volatile("{\n.reg .pred p;\nmbarrier.try_wait.parity.shared::cta.b64 p, [%1], %2;\nselp.u32 %0, 1, 0, p;\n}\n" : "=r"(ok) : "r"(bar), "r"(parity) : "memory");
  return ok;
}
__device__ __forceinline__ void spin_guard(uint32_t n) {
  asm volatile("{\n.reg .pred p;\n.reg .b32 a;\nmov.b32 a, 0x00fffffd;\nsetp.gt.u32 p, %0, %1;\n@p st.shared.u32 [a], %0;\n}\n" :: "r"(n), "n"(SPIN_LIMIT) : "memory");
}
__device__ __forceinline__ void mbar_wait(uint32_t bar, uint32_t parity) {
  asm volatile("{\n.reg .pred p, q;\n.reg .b32 n, a;\nmov.b32 n, 0;\nmov.b32 a, 0x00fffffd;\nWAIT_LOOP:\nadd.u32 n, n, 1;\nsetp.gt.u32 q, n, %2;\n@q st.shared.u32 [a], n;\n"
    "mbarrier.try_wait.parity.shared::cta.b64 p, [%0], %1;\n@!p bra WAIT_LOOP;\n}\n" :: "r"(bar), "r"(parity), "n"(SPIN_LIMIT) : "memory");
}
__device__ __forceinline__ void tma_load_2d(uint32_t dst, const CUtensorMap* tm, uint32_t bar, int c0, int c1) {
  asm volatile("cp.async.bulk.tensor.2d.shared::cluster.global.mbarrier::complete_tx::bytes [%0], [%1, {%3, %4}], [%2];"
    :: "r"(dst), "l"(tm), "r"(bar), "r"(c0), "r"(c1) : "memory");
}
__device__ __forceinline__ void tma_load_2d_mc(uint32_t dst, const CUtensorMap* tm, uint32_t bar, int c0, int c1, uint16_t mask) {
  asm volatile("cp.async.bulk.tensor.2d.shared::cluster.global.mbarrier::complete_tx::bytes.multicast::cluster [%0], [%1, {%3, %4}], [%2], %5;"
    :: "r"(dst), "l"(tm), "r"(bar), "r"(c0), "r"(c1), "h"(mask) : "memory");
}
__device__ __forceinline__ void tma_load_4d(uint32_t dst, const CUtensorMap* tm, uint32_t bar, int c1, int c2) {
  asm volatile("cp.async.bulk.tensor.4d.shared::cluster.global.mbarrier::complete_tx::bytes [%0], [%1, {%5, %3, %4, %5}], [%2];"
    :: "r"(dst), "l"(tm), "r"(bar), "r"(c1), "r"(c2), "r"(0) : "memory");
}
__device__ __forceinline__ void tma_store_2d(const CUtensorMap* tm, uint32_t src, int c0, int c1) {
  asm volatile("cp.async.bulk.tensor.2d.global.shared::cta.bulk_group [%0, {%2, %3}], [%1];" :: "l"(tm), "r"(src), "r"(c0), "r"(c1) : "memory");
}
__device__ __forceinline__ void bulk_commit() { asm volatile("cp.async.bulk.commit_group;" ::: "memory"); }
__device__ __forceinline__ void bulk_wait_read0() { asm volatile("cp.async.bulk.wait_group.read 0;" ::: "memory"); }
__device__ __forceinline__ void bulk_wait0() { asm volatile("cp.async.bulk.wait_group 0;" ::: "memory"); }
__device__ __forceinline__ void fence_async() { asm volatile("fence.proxy.async;" ::: "memory"); }
__device__ __forceinline__ void fence_async_smem() { asm volatile("fence.proxy.async.shared::cta;" ::: "memory"); }
__device__ __forceinline__ void prefetch_tmap(const CUtensorMap* tm) { asm volatile("prefetch.tensormap [%0];" :: "l"(tm) : "memory"); }
__device__ __forceinline__ void wgmma_fence() { asm volatile("wgmma.fence.sync.aligned;" ::: "memory"); }
__device__ __forceinline__ void wgmma_commit() { asm volatile("wgmma.commit_group.sync.aligned;" ::: "memory"); }
template<int N> __device__ __forceinline__ void wgmma_wait() { asm volatile("wgmma.wait_group.sync.aligned %0;" :: "n"(N) : "memory"); }
__device__ __forceinline__ uint32_t desc_lo(uint32_t addr, uint32_t lbo) { return (addr >> 4) | ((lbo >> 4) << 16); }
constexpr uint32_t H128 = 0x40000040u, H64 = 0x80000020u;
__device__ __forceinline__ void cluster_sync() {
  asm volatile("barrier.cluster.arrive.release.aligned;\nbarrier.cluster.wait.acquire.aligned;" ::: "memory");
}
__device__ __forceinline__ uint64_t gtimer() { uint64_t t; asm volatile("mov.u64 %0, %%globaltimer;" : "=l"(t)); return t; }
template<int R> __device__ __forceinline__ void reg_alloc() { asm volatile("setmaxnreg.inc.sync.aligned.u32 %0;" :: "n"(R)); }
template<int R> __device__ __forceinline__ void reg_dealloc() { asm volatile("setmaxnreg.dec.sync.aligned.u32 %0;" :: "n"(R)); }
__device__ __forceinline__ void bar_sync(int id, int n) { asm volatile("bar.sync %0, %1;" :: "r"(id), "r"(n) : "memory"); }
__device__ __forceinline__ uint32_t pack_bf16(float lo, float hi) { uint32_t r; asm("cvt.rn.bf16x2.f32 %0, %1, %2;" : "=r"(r) : "f"(hi), "f"(lo)); return r; }
__device__ __forceinline__ float bf_lo(uint32_t v) { return __uint_as_float(v << 16); }
__device__ __forceinline__ float bf_hi(uint32_t v) { return __uint_as_float(v & 0xffff0000u); }
__device__ __forceinline__ float bf_round(float v) { return bf_lo(pack_bf16(v, 0.f)); }
__device__ __forceinline__ void stmatrix_x4(uint32_t addr, uint32_t r0, uint32_t r1, uint32_t r2, uint32_t r3) {
  asm volatile("stmatrix.sync.aligned.m8n8.x4.shared.b16 [%0], {%1, %2, %3, %4};" :: "r"(addr), "r"(r0), "r"(r1), "r"(r2), "r"(r3) : "memory");
}
__device__ __forceinline__ void ldmatrix_x4(uint32_t addr, uint32_t& r0, uint32_t& r1, uint32_t& r2, uint32_t& r3) {
  asm volatile("ldmatrix.sync.aligned.m8n8.x4.shared.b16 {%0, %1, %2, %3}, [%4];" : "=r"(r0), "=r"(r1), "=r"(r2), "=r"(r3) : "r"(addr) : "memory");
}
__device__ __forceinline__ uint32_t ld_acquire(const uint32_t* p) { uint32_t v; asm volatile("ld.acquire.gpu.global.u32 %0, [%1];" : "=r"(v) : "l"(p) : "memory"); return v; }
__device__ __forceinline__ uint32_t ld_relaxed(const uint32_t* p) { uint32_t v; asm volatile("ld.relaxed.gpu.global.u32 %0, [%1];" : "=r"(v) : "l"(p) : "memory"); return v; }
__device__ __forceinline__ void st_release(uint32_t* p, uint32_t v) { asm volatile("st.release.gpu.global.u32 [%0], %1;" :: "l"(p), "r"(v) : "memory"); }
__device__ __forceinline__ uint4 ld_vol4(const void* p) { uint4 v; asm volatile("ld.volatile.global.v4.u32 {%0, %1, %2, %3}, [%4];" : "=r"(v.x), "=r"(v.y), "=r"(v.z), "=r"(v.w) : "l"(p) : "memory"); return v; }
__device__ __forceinline__ uint2 ld_vol2(const void* p) { uint2 v; asm volatile("ld.volatile.global.v2.u32 {%0, %1}, [%2];" : "=r"(v.x), "=r"(v.y) : "l"(p) : "memory"); return v; }
__device__ __forceinline__ void st_vol2(void* p, uint32_t a, uint32_t b) { asm volatile("st.volatile.global.v2.u32 [%0], {%1, %2};" :: "l"(p), "r"(a), "r"(b) : "memory"); }
__device__ __forceinline__ void st_vol4(void* p, uint32_t a, uint32_t b, uint32_t c, uint32_t d) { asm volatile("st.volatile.global.v4.u32 [%0], {%1, %2, %3, %4};" :: "l"(p), "r"(a), "r"(b), "r"(c), "r"(d) : "memory"); }
__device__ __forceinline__ uint4 ld_nc4(const void* p) { uint4 v; asm volatile("ld.global.nc.L1::no_allocate.v4.u32 {%0, %1, %2, %3}, [%4];" : "=r"(v.x), "=r"(v.y), "=r"(v.z), "=r"(v.w) : "l"(p)); return v; }
__device__ __forceinline__ uint32_t ld_nc1(const void* p) { uint32_t v; asm volatile("ld.global.nc.u32 %0, [%1];" : "=r"(v) : "l"(p)); return v; }
__device__ __forceinline__ void red_add4(float4* p, float a, float b, float c, float d) {
  asm volatile("red.global.add.v4.f32 [%0], {%1, %2, %3, %4};" :: "l"(p), "f"(a), "f"(b), "f"(c), "f"(d) : "memory");
}
__device__ __forceinline__ void sts4(uint32_t a, uint32_t x, uint32_t y, uint32_t z, uint32_t w) { asm volatile("st.shared.v4.u32 [%0], {%1, %2, %3, %4};" :: "r"(a), "r"(x), "r"(y), "r"(z), "r"(w) : "memory"); }
__device__ __forceinline__ void sts2(uint32_t a, uint32_t x, uint32_t y) { asm volatile("st.shared.v2.u32 [%0], {%1, %2};" :: "r"(a), "r"(x), "r"(y) : "memory"); }
__device__ __forceinline__ void sts1(uint32_t a, uint32_t x) { asm volatile("st.shared.u32 [%0], %1;" :: "r"(a), "r"(x) : "memory"); }
__device__ __forceinline__ uint4 lds4(uint32_t a) { uint4 v; asm volatile("ld.shared.v4.u32 {%0, %1, %2, %3}, [%4];" : "=r"(v.x), "=r"(v.y), "=r"(v.z), "=r"(v.w) : "r"(a) : "memory"); return v; }
__device__ __forceinline__ uint2 lds2(uint32_t a) { uint2 v; asm volatile("ld.shared.v2.u32 {%0, %1}, [%2];" : "=r"(v.x), "=r"(v.y) : "r"(a) : "memory"); return v; }
__device__ __forceinline__ uint32_t lds1(uint32_t a) { uint32_t v; asm volatile("ld.shared.u32 %0, [%1];" : "=r"(v) : "r"(a) : "memory"); return v; }
__device__ __forceinline__ float ex2(float x) { float y; asm("ex2.approx.ftz.f32 %0, %1;" : "=f"(y) : "f"(x)); return y; }
__device__ __forceinline__ float rcp(float x) { float y; asm("rcp.approx.ftz.f32 %0, %1;" : "=f"(y) : "f"(x)); return y; }
__device__ __forceinline__ void prefetch_l2(const void* p) { asm volatile("prefetch.global.L2 [%0];" :: "l"(p)); }

__device__ __forceinline__ void st_relaxed(uint32_t* p, uint32_t v) { asm volatile("st.relaxed.gpu.global.u32 [%0], %1;" :: "l"(p), "r"(v) : "memory"); }
__device__ __forceinline__ uint4 ld_nc4p(const void* p) { uint4 v; asm volatile("ld.global.nc.L1::no_allocate.L2::128B.v4.u32 {%0, %1, %2, %3}, [%4];" : "=r"(v.x), "=r"(v.y), "=r"(v.z), "=r"(v.w) : "l"(p)); return v; }
__device__ __forceinline__ uint32_t mapa(uint32_t a, uint32_t cta) { uint32_t r; asm("mapa.shared::cluster.u32 %0, %1, %2;" : "=r"(r) : "r"(a), "r"(cta)); return r; }
__device__ __forceinline__ void mbar_arrive_cl(uint32_t a) { asm volatile("mbarrier.arrive.shared::cluster.b64 _, [%0];" :: "r"(a) : "memory"); }
__device__ __forceinline__ void bulk_load_mc(uint32_t dst, const void* src, uint32_t bytes, uint32_t bar) {
  asm volatile("cp.async.bulk.shared::cluster.global.mbarrier::complete_tx::bytes.multicast::cluster [%0], [%1], %2, [%3], %4;"
    :: "r"(dst), "l"(src), "r"(bytes), "r"(bar), "h"((uint16_t)3) : "memory");
}
__device__ __forceinline__ void bulk_store(void* dst, uint32_t src, uint32_t bytes) {
  asm volatile("cp.async.bulk.global.shared::cta.bulk_group [%0], [%1], %2;" :: "l"(dst), "r"(src), "r"(bytes) : "memory");
}
__device__ __forceinline__ void bulk_copy_peer(uint32_t dst, uint32_t src, uint32_t bytes, uint32_t bar) {
  asm volatile("cp.async.bulk.shared::cluster.shared::cta.mbarrier::complete_tx::bytes [%0], [%1], %2, [%3];" :: "r"(dst), "r"(src), "r"(bytes), "r"(bar) : "memory");
}
__device__ __forceinline__ void bulk_prefetch(const void* src, uint32_t bytes) { asm volatile("cp.async.bulk.prefetch.L2.global [%0], %1;" :: "l"(src), "r"(bytes) : "memory"); }
__device__ __forceinline__ void bulk_wait1() { asm volatile("cp.async.bulk.wait_group 1;" ::: "memory"); }
__device__ __forceinline__ void cluster_arrive() { asm volatile("barrier.cluster.arrive.relaxed.aligned;" ::: "memory"); }
__device__ __forceinline__ void cluster_wait() { asm volatile("barrier.cluster.wait.aligned;" ::: "memory"); }
__device__ __forceinline__ uint32_t hfma2(uint32_t a, uint32_t b, uint32_t c) { uint32_t r; asm("fma.rn.bf16x2 %0, %1, %2, %3;" : "=r"(r) : "r"(a), "r"(b), "r"(c)); return r; }
__device__ __forceinline__ uint32_t hmul2(uint32_t a, uint32_t b) { uint32_t r; asm("mul.rn.bf16x2 %0, %1, %2;" : "=r"(r) : "r"(a), "r"(b)); return r; }
__device__ __forceinline__ uint32_t pack_relu(float lo, float hi) { uint32_t r; asm("cvt.rn.relu.bf16x2.f32 %0, %1, %2;" : "=r"(r) : "f"(hi), "f"(lo)); return r; }
__device__ __forceinline__ uint2 ld_nc2(const void* p) { uint2 v; asm volatile("ld.global.nc.L1::no_allocate.v2.u32 {%0, %1}, [%2];" : "=r"(v.x), "=r"(v.y) : "l"(p)); return v; }
__device__ __forceinline__ void hmma(float (&d)[4], uint32_t a0, uint32_t a1, uint32_t a2, uint32_t a3, uint32_t b0, uint32_t b1) {
  asm("mma.sync.aligned.m16n8k16.row.col.f32.bf16.bf16.f32 {%0, %1, %2, %3}, {%4, %5, %6, %7}, {%8, %9}, {%0, %1, %2, %3};"
    : "+f"(d[0]), "+f"(d[1]), "+f"(d[2]), "+f"(d[3]) : "r"(a0), "r"(a1), "r"(a2), "r"(a3), "r"(b0), "r"(b1));
}
template<int N> __device__ __forceinline__ void fence_regs(float (&r)[N]) {
#pragma unroll
  for (int i = 0; i < N; i++) asm volatile("" : "+f"(r[i]) :: "memory");
}

template<int N> __device__ __forceinline__ void zero_regs(float (&r)[N]) {
#pragma unroll
  for (int i = 0; i < N; i++) asm volatile("mov.f32 %0, 0f00000000;" : "=f"(r[i]));
}

template<int TA, int TB, uint32_t HI> __device__ __forceinline__ void wgmma_ss_n192(float (&d)[96], uint32_t da, uint32_t db) {
  asm volatile("{\n.reg .pred p;\n.reg .b64 da, db;\nsetp.ne.b32 p, 1, 0;\nmov.b64 da, {%96, %100};\nmov.b64 db, {%97, %100};\n"
    "wgmma.mma_async.sync.aligned.m64n192k16.f32.bf16.bf16 {%0, %1, %2, %3, %4, %5, %6, %7, %8, %9, %10, %11, %12, %13, %14, %15, %16, %17, %18, %19, %20, %21, %22, %23, %24, %25, %26, %27, %28, %29, %30, %31, %32, %33, %34, %35, %36, %37, %38, %39, %40, %41, %42, %43, %44, %45, %46, %47, %48, %49, %50, %51, %52, %53, %54, %55, %56, %57, %58, %59, %60, %61, %62, %63, %64, %65, %66, %67, %68, %69, %70, %71, %72, %73, %74, %75, %76, %77, %78, %79, %80, %81, %82, %83, %84, %85, %86, %87, %88, %89, %90, %91, %92, %93, %94, %95}, da, db, p, 1, 1, %98, %99;\n}\n"
    : "+f"(d[0]), "+f"(d[1]), "+f"(d[2]), "+f"(d[3]), "+f"(d[4]), "+f"(d[5]), "+f"(d[6]), "+f"(d[7]), "+f"(d[8]), "+f"(d[9]), "+f"(d[10]), "+f"(d[11]), "+f"(d[12]), "+f"(d[13]), "+f"(d[14]), "+f"(d[15]), "+f"(d[16]), "+f"(d[17]), "+f"(d[18]), "+f"(d[19]), "+f"(d[20]), "+f"(d[21]), "+f"(d[22]), "+f"(d[23]), "+f"(d[24]), "+f"(d[25]), "+f"(d[26]), "+f"(d[27]), "+f"(d[28]), "+f"(d[29]), "+f"(d[30]), "+f"(d[31]), "+f"(d[32]), "+f"(d[33]), "+f"(d[34]), "+f"(d[35]), "+f"(d[36]), "+f"(d[37]), "+f"(d[38]), "+f"(d[39]), "+f"(d[40]), "+f"(d[41]), "+f"(d[42]), "+f"(d[43]), "+f"(d[44]), "+f"(d[45]), "+f"(d[46]), "+f"(d[47]), "+f"(d[48]), "+f"(d[49]), "+f"(d[50]), "+f"(d[51]), "+f"(d[52]), "+f"(d[53]), "+f"(d[54]), "+f"(d[55]), "+f"(d[56]), "+f"(d[57]), "+f"(d[58]), "+f"(d[59]), "+f"(d[60]), "+f"(d[61]), "+f"(d[62]), "+f"(d[63]), "+f"(d[64]), "+f"(d[65]), "+f"(d[66]), "+f"(d[67]), "+f"(d[68]), "+f"(d[69]), "+f"(d[70]), "+f"(d[71]), "+f"(d[72]), "+f"(d[73]), "+f"(d[74]), "+f"(d[75]), "+f"(d[76]), "+f"(d[77]), "+f"(d[78]), "+f"(d[79]), "+f"(d[80]), "+f"(d[81]), "+f"(d[82]), "+f"(d[83]), "+f"(d[84]), "+f"(d[85]), "+f"(d[86]), "+f"(d[87]), "+f"(d[88]), "+f"(d[89]), "+f"(d[90]), "+f"(d[91]), "+f"(d[92]), "+f"(d[93]), "+f"(d[94]), "+f"(d[95])
    : "r"(da), "r"(db), "n"(TA), "n"(TB), "n"(HI));
}
template<int TA, int TB, uint32_t HI> __device__ __forceinline__ void wgmma_ssz_n192(float (&d)[96], uint32_t da, uint32_t db) {
  asm volatile("{\n.reg .pred p;\n.reg .b64 da, db;\nsetp.ne.b32 p, 0, 0;\nmov.b64 da, {%96, %100};\nmov.b64 db, {%97, %100};\n"
    "wgmma.mma_async.sync.aligned.m64n192k16.f32.bf16.bf16 {%0, %1, %2, %3, %4, %5, %6, %7, %8, %9, %10, %11, %12, %13, %14, %15, %16, %17, %18, %19, %20, %21, %22, %23, %24, %25, %26, %27, %28, %29, %30, %31, %32, %33, %34, %35, %36, %37, %38, %39, %40, %41, %42, %43, %44, %45, %46, %47, %48, %49, %50, %51, %52, %53, %54, %55, %56, %57, %58, %59, %60, %61, %62, %63, %64, %65, %66, %67, %68, %69, %70, %71, %72, %73, %74, %75, %76, %77, %78, %79, %80, %81, %82, %83, %84, %85, %86, %87, %88, %89, %90, %91, %92, %93, %94, %95}, da, db, p, 1, 1, %98, %99;\n}\n"
    : "=f"(d[0]), "=f"(d[1]), "=f"(d[2]), "=f"(d[3]), "=f"(d[4]), "=f"(d[5]), "=f"(d[6]), "=f"(d[7]), "=f"(d[8]), "=f"(d[9]), "=f"(d[10]), "=f"(d[11]), "=f"(d[12]), "=f"(d[13]), "=f"(d[14]), "=f"(d[15]), "=f"(d[16]), "=f"(d[17]), "=f"(d[18]), "=f"(d[19]), "=f"(d[20]), "=f"(d[21]), "=f"(d[22]), "=f"(d[23]), "=f"(d[24]), "=f"(d[25]), "=f"(d[26]), "=f"(d[27]), "=f"(d[28]), "=f"(d[29]), "=f"(d[30]), "=f"(d[31]), "=f"(d[32]), "=f"(d[33]), "=f"(d[34]), "=f"(d[35]), "=f"(d[36]), "=f"(d[37]), "=f"(d[38]), "=f"(d[39]), "=f"(d[40]), "=f"(d[41]), "=f"(d[42]), "=f"(d[43]), "=f"(d[44]), "=f"(d[45]), "=f"(d[46]), "=f"(d[47]), "=f"(d[48]), "=f"(d[49]), "=f"(d[50]), "=f"(d[51]), "=f"(d[52]), "=f"(d[53]), "=f"(d[54]), "=f"(d[55]), "=f"(d[56]), "=f"(d[57]), "=f"(d[58]), "=f"(d[59]), "=f"(d[60]), "=f"(d[61]), "=f"(d[62]), "=f"(d[63]), "=f"(d[64]), "=f"(d[65]), "=f"(d[66]), "=f"(d[67]), "=f"(d[68]), "=f"(d[69]), "=f"(d[70]), "=f"(d[71]), "=f"(d[72]), "=f"(d[73]), "=f"(d[74]), "=f"(d[75]), "=f"(d[76]), "=f"(d[77]), "=f"(d[78]), "=f"(d[79]), "=f"(d[80]), "=f"(d[81]), "=f"(d[82]), "=f"(d[83]), "=f"(d[84]), "=f"(d[85]), "=f"(d[86]), "=f"(d[87]), "=f"(d[88]), "=f"(d[89]), "=f"(d[90]), "=f"(d[91]), "=f"(d[92]), "=f"(d[93]), "=f"(d[94]), "=f"(d[95])
    : "r"(da), "r"(db), "n"(TA), "n"(TB), "n"(HI));
}
template<int TA, int TB, uint32_t HI> __device__ __forceinline__ void wgmma_ss_n128(float (&d)[64], uint32_t da, uint32_t db) {
  asm volatile("{\n.reg .pred p;\n.reg .b64 da, db;\nsetp.ne.b32 p, 1, 0;\nmov.b64 da, {%64, %68};\nmov.b64 db, {%65, %68};\n"
    "wgmma.mma_async.sync.aligned.m64n128k16.f32.bf16.bf16 {%0, %1, %2, %3, %4, %5, %6, %7, %8, %9, %10, %11, %12, %13, %14, %15, %16, %17, %18, %19, %20, %21, %22, %23, %24, %25, %26, %27, %28, %29, %30, %31, %32, %33, %34, %35, %36, %37, %38, %39, %40, %41, %42, %43, %44, %45, %46, %47, %48, %49, %50, %51, %52, %53, %54, %55, %56, %57, %58, %59, %60, %61, %62, %63}, da, db, p, 1, 1, %66, %67;\n}\n"
    : "+f"(d[0]), "+f"(d[1]), "+f"(d[2]), "+f"(d[3]), "+f"(d[4]), "+f"(d[5]), "+f"(d[6]), "+f"(d[7]), "+f"(d[8]), "+f"(d[9]), "+f"(d[10]), "+f"(d[11]), "+f"(d[12]), "+f"(d[13]), "+f"(d[14]), "+f"(d[15]), "+f"(d[16]), "+f"(d[17]), "+f"(d[18]), "+f"(d[19]), "+f"(d[20]), "+f"(d[21]), "+f"(d[22]), "+f"(d[23]), "+f"(d[24]), "+f"(d[25]), "+f"(d[26]), "+f"(d[27]), "+f"(d[28]), "+f"(d[29]), "+f"(d[30]), "+f"(d[31]), "+f"(d[32]), "+f"(d[33]), "+f"(d[34]), "+f"(d[35]), "+f"(d[36]), "+f"(d[37]), "+f"(d[38]), "+f"(d[39]), "+f"(d[40]), "+f"(d[41]), "+f"(d[42]), "+f"(d[43]), "+f"(d[44]), "+f"(d[45]), "+f"(d[46]), "+f"(d[47]), "+f"(d[48]), "+f"(d[49]), "+f"(d[50]), "+f"(d[51]), "+f"(d[52]), "+f"(d[53]), "+f"(d[54]), "+f"(d[55]), "+f"(d[56]), "+f"(d[57]), "+f"(d[58]), "+f"(d[59]), "+f"(d[60]), "+f"(d[61]), "+f"(d[62]), "+f"(d[63])
    : "r"(da), "r"(db), "n"(TA), "n"(TB), "n"(HI));
}
template<int TA, int TB, uint32_t HI> __device__ __forceinline__ void wgmma_ssz_n128(float (&d)[64], uint32_t da, uint32_t db) {
  asm volatile("{\n.reg .pred p;\n.reg .b64 da, db;\nsetp.ne.b32 p, 0, 0;\nmov.b64 da, {%64, %68};\nmov.b64 db, {%65, %68};\n"
    "wgmma.mma_async.sync.aligned.m64n128k16.f32.bf16.bf16 {%0, %1, %2, %3, %4, %5, %6, %7, %8, %9, %10, %11, %12, %13, %14, %15, %16, %17, %18, %19, %20, %21, %22, %23, %24, %25, %26, %27, %28, %29, %30, %31, %32, %33, %34, %35, %36, %37, %38, %39, %40, %41, %42, %43, %44, %45, %46, %47, %48, %49, %50, %51, %52, %53, %54, %55, %56, %57, %58, %59, %60, %61, %62, %63}, da, db, p, 1, 1, %66, %67;\n}\n"
    : "=f"(d[0]), "=f"(d[1]), "=f"(d[2]), "=f"(d[3]), "=f"(d[4]), "=f"(d[5]), "=f"(d[6]), "=f"(d[7]), "=f"(d[8]), "=f"(d[9]), "=f"(d[10]), "=f"(d[11]), "=f"(d[12]), "=f"(d[13]), "=f"(d[14]), "=f"(d[15]), "=f"(d[16]), "=f"(d[17]), "=f"(d[18]), "=f"(d[19]), "=f"(d[20]), "=f"(d[21]), "=f"(d[22]), "=f"(d[23]), "=f"(d[24]), "=f"(d[25]), "=f"(d[26]), "=f"(d[27]), "=f"(d[28]), "=f"(d[29]), "=f"(d[30]), "=f"(d[31]), "=f"(d[32]), "=f"(d[33]), "=f"(d[34]), "=f"(d[35]), "=f"(d[36]), "=f"(d[37]), "=f"(d[38]), "=f"(d[39]), "=f"(d[40]), "=f"(d[41]), "=f"(d[42]), "=f"(d[43]), "=f"(d[44]), "=f"(d[45]), "=f"(d[46]), "=f"(d[47]), "=f"(d[48]), "=f"(d[49]), "=f"(d[50]), "=f"(d[51]), "=f"(d[52]), "=f"(d[53]), "=f"(d[54]), "=f"(d[55]), "=f"(d[56]), "=f"(d[57]), "=f"(d[58]), "=f"(d[59]), "=f"(d[60]), "=f"(d[61]), "=f"(d[62]), "=f"(d[63])
    : "r"(da), "r"(db), "n"(TA), "n"(TB), "n"(HI));
}
template<int TA, int TB, uint32_t HI> __device__ __forceinline__ void wgmma_ssp_n128(float (&d)[64], uint32_t da, uint32_t db, uint32_t sd) {
  asm volatile("{\n.reg .pred p;\n.reg .b64 da, db;\nsetp.ne.b32 p, %69, 0;\nmov.b64 da, {%64, %68};\nmov.b64 db, {%65, %68};\n"
    "wgmma.mma_async.sync.aligned.m64n128k16.f32.bf16.bf16 {%0, %1, %2, %3, %4, %5, %6, %7, %8, %9, %10, %11, %12, %13, %14, %15, %16, %17, %18, %19, %20, %21, %22, %23, %24, %25, %26, %27, %28, %29, %30, %31, %32, %33, %34, %35, %36, %37, %38, %39, %40, %41, %42, %43, %44, %45, %46, %47, %48, %49, %50, %51, %52, %53, %54, %55, %56, %57, %58, %59, %60, %61, %62, %63}, da, db, p, 1, 1, %66, %67;\n}\n"
    : "+f"(d[0]), "+f"(d[1]), "+f"(d[2]), "+f"(d[3]), "+f"(d[4]), "+f"(d[5]), "+f"(d[6]), "+f"(d[7]), "+f"(d[8]), "+f"(d[9]), "+f"(d[10]), "+f"(d[11]), "+f"(d[12]), "+f"(d[13]), "+f"(d[14]), "+f"(d[15]), "+f"(d[16]), "+f"(d[17]), "+f"(d[18]), "+f"(d[19]), "+f"(d[20]), "+f"(d[21]), "+f"(d[22]), "+f"(d[23]), "+f"(d[24]), "+f"(d[25]), "+f"(d[26]), "+f"(d[27]), "+f"(d[28]), "+f"(d[29]), "+f"(d[30]), "+f"(d[31]), "+f"(d[32]), "+f"(d[33]), "+f"(d[34]), "+f"(d[35]), "+f"(d[36]), "+f"(d[37]), "+f"(d[38]), "+f"(d[39]), "+f"(d[40]), "+f"(d[41]), "+f"(d[42]), "+f"(d[43]), "+f"(d[44]), "+f"(d[45]), "+f"(d[46]), "+f"(d[47]), "+f"(d[48]), "+f"(d[49]), "+f"(d[50]), "+f"(d[51]), "+f"(d[52]), "+f"(d[53]), "+f"(d[54]), "+f"(d[55]), "+f"(d[56]), "+f"(d[57]), "+f"(d[58]), "+f"(d[59]), "+f"(d[60]), "+f"(d[61]), "+f"(d[62]), "+f"(d[63])
    : "r"(da), "r"(db), "n"(TA), "n"(TB), "n"(HI), "r"(sd));
}
template<int TA, int TB, uint32_t HI> __device__ __forceinline__ void wgmma_ss_n40(float (&d)[20], uint32_t da, uint32_t db) {
  asm volatile("{\n.reg .pred p;\n.reg .b64 da, db;\nsetp.ne.b32 p, 1, 0;\nmov.b64 da, {%20, %24};\nmov.b64 db, {%21, %24};\n"
    "wgmma.mma_async.sync.aligned.m64n40k16.f32.bf16.bf16 {%0, %1, %2, %3, %4, %5, %6, %7, %8, %9, %10, %11, %12, %13, %14, %15, %16, %17, %18, %19}, da, db, p, 1, 1, %22, %23;\n}\n"
    : "+f"(d[0]), "+f"(d[1]), "+f"(d[2]), "+f"(d[3]), "+f"(d[4]), "+f"(d[5]), "+f"(d[6]), "+f"(d[7]), "+f"(d[8]), "+f"(d[9]), "+f"(d[10]), "+f"(d[11]), "+f"(d[12]), "+f"(d[13]), "+f"(d[14]), "+f"(d[15]), "+f"(d[16]), "+f"(d[17]), "+f"(d[18]), "+f"(d[19])
    : "r"(da), "r"(db), "n"(TA), "n"(TB), "n"(HI));
}
template<int TA, int TB, uint32_t HI> __device__ __forceinline__ void wgmma_ssz_n40(float (&d)[20], uint32_t da, uint32_t db) {
  asm volatile("{\n.reg .pred p;\n.reg .b64 da, db;\nsetp.ne.b32 p, 0, 0;\nmov.b64 da, {%20, %24};\nmov.b64 db, {%21, %24};\n"
    "wgmma.mma_async.sync.aligned.m64n40k16.f32.bf16.bf16 {%0, %1, %2, %3, %4, %5, %6, %7, %8, %9, %10, %11, %12, %13, %14, %15, %16, %17, %18, %19}, da, db, p, 1, 1, %22, %23;\n}\n"
    : "=f"(d[0]), "=f"(d[1]), "=f"(d[2]), "=f"(d[3]), "=f"(d[4]), "=f"(d[5]), "=f"(d[6]), "=f"(d[7]), "=f"(d[8]), "=f"(d[9]), "=f"(d[10]), "=f"(d[11]), "=f"(d[12]), "=f"(d[13]), "=f"(d[14]), "=f"(d[15]), "=f"(d[16]), "=f"(d[17]), "=f"(d[18]), "=f"(d[19])
    : "r"(da), "r"(db), "n"(TA), "n"(TB), "n"(HI));
}
template<int TB, uint32_t HI> __device__ __forceinline__ void wgmma_rs_n256(float (&d)[128], uint32_t a0, uint32_t a1, uint32_t a2, uint32_t a3, uint32_t db) {
  asm volatile("{\n.reg .pred p;\n.reg .b64 db;\nsetp.ne.b32 p, 1, 0;\nmov.b64 db, {%132, %134};\n"
    "wgmma.mma_async.sync.aligned.m64n256k16.f32.bf16.bf16 {%0, %1, %2, %3, %4, %5, %6, %7, %8, %9, %10, %11, %12, %13, %14, %15, %16, %17, %18, %19, %20, %21, %22, %23, %24, %25, %26, %27, %28, %29, %30, %31, %32, %33, %34, %35, %36, %37, %38, %39, %40, %41, %42, %43, %44, %45, %46, %47, %48, %49, %50, %51, %52, %53, %54, %55, %56, %57, %58, %59, %60, %61, %62, %63, %64, %65, %66, %67, %68, %69, %70, %71, %72, %73, %74, %75, %76, %77, %78, %79, %80, %81, %82, %83, %84, %85, %86, %87, %88, %89, %90, %91, %92, %93, %94, %95, %96, %97, %98, %99, %100, %101, %102, %103, %104, %105, %106, %107, %108, %109, %110, %111, %112, %113, %114, %115, %116, %117, %118, %119, %120, %121, %122, %123, %124, %125, %126, %127}, {%128, %129, %130, %131}, db, p, 1, 1, %133;\n}\n"
    : "+f"(d[0]), "+f"(d[1]), "+f"(d[2]), "+f"(d[3]), "+f"(d[4]), "+f"(d[5]), "+f"(d[6]), "+f"(d[7]), "+f"(d[8]), "+f"(d[9]), "+f"(d[10]), "+f"(d[11]), "+f"(d[12]), "+f"(d[13]), "+f"(d[14]), "+f"(d[15]), "+f"(d[16]), "+f"(d[17]), "+f"(d[18]), "+f"(d[19]), "+f"(d[20]), "+f"(d[21]), "+f"(d[22]), "+f"(d[23]), "+f"(d[24]), "+f"(d[25]), "+f"(d[26]), "+f"(d[27]), "+f"(d[28]), "+f"(d[29]), "+f"(d[30]), "+f"(d[31]), "+f"(d[32]), "+f"(d[33]), "+f"(d[34]), "+f"(d[35]), "+f"(d[36]), "+f"(d[37]), "+f"(d[38]), "+f"(d[39]), "+f"(d[40]), "+f"(d[41]), "+f"(d[42]), "+f"(d[43]), "+f"(d[44]), "+f"(d[45]), "+f"(d[46]), "+f"(d[47]), "+f"(d[48]), "+f"(d[49]), "+f"(d[50]), "+f"(d[51]), "+f"(d[52]), "+f"(d[53]), "+f"(d[54]), "+f"(d[55]), "+f"(d[56]), "+f"(d[57]), "+f"(d[58]), "+f"(d[59]), "+f"(d[60]), "+f"(d[61]), "+f"(d[62]), "+f"(d[63]), "+f"(d[64]), "+f"(d[65]), "+f"(d[66]), "+f"(d[67]), "+f"(d[68]), "+f"(d[69]), "+f"(d[70]), "+f"(d[71]), "+f"(d[72]), "+f"(d[73]), "+f"(d[74]), "+f"(d[75]), "+f"(d[76]), "+f"(d[77]), "+f"(d[78]), "+f"(d[79]), "+f"(d[80]), "+f"(d[81]), "+f"(d[82]), "+f"(d[83]), "+f"(d[84]), "+f"(d[85]), "+f"(d[86]), "+f"(d[87]), "+f"(d[88]), "+f"(d[89]), "+f"(d[90]), "+f"(d[91]), "+f"(d[92]), "+f"(d[93]), "+f"(d[94]), "+f"(d[95]), "+f"(d[96]), "+f"(d[97]), "+f"(d[98]), "+f"(d[99]), "+f"(d[100]), "+f"(d[101]), "+f"(d[102]), "+f"(d[103]), "+f"(d[104]), "+f"(d[105]), "+f"(d[106]), "+f"(d[107]), "+f"(d[108]), "+f"(d[109]), "+f"(d[110]), "+f"(d[111]), "+f"(d[112]), "+f"(d[113]), "+f"(d[114]), "+f"(d[115]), "+f"(d[116]), "+f"(d[117]), "+f"(d[118]), "+f"(d[119]), "+f"(d[120]), "+f"(d[121]), "+f"(d[122]), "+f"(d[123]), "+f"(d[124]), "+f"(d[125]), "+f"(d[126]), "+f"(d[127])
    : "r"(a0), "r"(a1), "r"(a2), "r"(a3), "r"(db), "n"(TB), "n"(HI));
}
template<int TB, uint32_t HI> __device__ __forceinline__ void wgmma_rsz_n256(float (&d)[128], uint32_t a0, uint32_t a1, uint32_t a2, uint32_t a3, uint32_t db) {
  asm volatile("{\n.reg .pred p;\n.reg .b64 db;\nsetp.ne.b32 p, 0, 0;\nmov.b64 db, {%132, %134};\n"
    "wgmma.mma_async.sync.aligned.m64n256k16.f32.bf16.bf16 {%0, %1, %2, %3, %4, %5, %6, %7, %8, %9, %10, %11, %12, %13, %14, %15, %16, %17, %18, %19, %20, %21, %22, %23, %24, %25, %26, %27, %28, %29, %30, %31, %32, %33, %34, %35, %36, %37, %38, %39, %40, %41, %42, %43, %44, %45, %46, %47, %48, %49, %50, %51, %52, %53, %54, %55, %56, %57, %58, %59, %60, %61, %62, %63, %64, %65, %66, %67, %68, %69, %70, %71, %72, %73, %74, %75, %76, %77, %78, %79, %80, %81, %82, %83, %84, %85, %86, %87, %88, %89, %90, %91, %92, %93, %94, %95, %96, %97, %98, %99, %100, %101, %102, %103, %104, %105, %106, %107, %108, %109, %110, %111, %112, %113, %114, %115, %116, %117, %118, %119, %120, %121, %122, %123, %124, %125, %126, %127}, {%128, %129, %130, %131}, db, p, 1, 1, %133;\n}\n"
    : "=f"(d[0]), "=f"(d[1]), "=f"(d[2]), "=f"(d[3]), "=f"(d[4]), "=f"(d[5]), "=f"(d[6]), "=f"(d[7]), "=f"(d[8]), "=f"(d[9]), "=f"(d[10]), "=f"(d[11]), "=f"(d[12]), "=f"(d[13]), "=f"(d[14]), "=f"(d[15]), "=f"(d[16]), "=f"(d[17]), "=f"(d[18]), "=f"(d[19]), "=f"(d[20]), "=f"(d[21]), "=f"(d[22]), "=f"(d[23]), "=f"(d[24]), "=f"(d[25]), "=f"(d[26]), "=f"(d[27]), "=f"(d[28]), "=f"(d[29]), "=f"(d[30]), "=f"(d[31]), "=f"(d[32]), "=f"(d[33]), "=f"(d[34]), "=f"(d[35]), "=f"(d[36]), "=f"(d[37]), "=f"(d[38]), "=f"(d[39]), "=f"(d[40]), "=f"(d[41]), "=f"(d[42]), "=f"(d[43]), "=f"(d[44]), "=f"(d[45]), "=f"(d[46]), "=f"(d[47]), "=f"(d[48]), "=f"(d[49]), "=f"(d[50]), "=f"(d[51]), "=f"(d[52]), "=f"(d[53]), "=f"(d[54]), "=f"(d[55]), "=f"(d[56]), "=f"(d[57]), "=f"(d[58]), "=f"(d[59]), "=f"(d[60]), "=f"(d[61]), "=f"(d[62]), "=f"(d[63]), "=f"(d[64]), "=f"(d[65]), "=f"(d[66]), "=f"(d[67]), "=f"(d[68]), "=f"(d[69]), "=f"(d[70]), "=f"(d[71]), "=f"(d[72]), "=f"(d[73]), "=f"(d[74]), "=f"(d[75]), "=f"(d[76]), "=f"(d[77]), "=f"(d[78]), "=f"(d[79]), "=f"(d[80]), "=f"(d[81]), "=f"(d[82]), "=f"(d[83]), "=f"(d[84]), "=f"(d[85]), "=f"(d[86]), "=f"(d[87]), "=f"(d[88]), "=f"(d[89]), "=f"(d[90]), "=f"(d[91]), "=f"(d[92]), "=f"(d[93]), "=f"(d[94]), "=f"(d[95]), "=f"(d[96]), "=f"(d[97]), "=f"(d[98]), "=f"(d[99]), "=f"(d[100]), "=f"(d[101]), "=f"(d[102]), "=f"(d[103]), "=f"(d[104]), "=f"(d[105]), "=f"(d[106]), "=f"(d[107]), "=f"(d[108]), "=f"(d[109]), "=f"(d[110]), "=f"(d[111]), "=f"(d[112]), "=f"(d[113]), "=f"(d[114]), "=f"(d[115]), "=f"(d[116]), "=f"(d[117]), "=f"(d[118]), "=f"(d[119]), "=f"(d[120]), "=f"(d[121]), "=f"(d[122]), "=f"(d[123]), "=f"(d[124]), "=f"(d[125]), "=f"(d[126]), "=f"(d[127])
    : "r"(a0), "r"(a1), "r"(a2), "r"(a3), "r"(db), "n"(TB), "n"(HI));
}
template<int TB, uint32_t HI> __device__ __forceinline__ void wgmma_rs_n40(float (&d)[20], uint32_t a0, uint32_t a1, uint32_t a2, uint32_t a3, uint32_t db) {
  asm volatile("{\n.reg .pred p;\n.reg .b64 db;\nsetp.ne.b32 p, 1, 0;\nmov.b64 db, {%24, %26};\n"
    "wgmma.mma_async.sync.aligned.m64n40k16.f32.bf16.bf16 {%0, %1, %2, %3, %4, %5, %6, %7, %8, %9, %10, %11, %12, %13, %14, %15, %16, %17, %18, %19}, {%20, %21, %22, %23}, db, p, 1, 1, %25;\n}\n"
    : "+f"(d[0]), "+f"(d[1]), "+f"(d[2]), "+f"(d[3]), "+f"(d[4]), "+f"(d[5]), "+f"(d[6]), "+f"(d[7]), "+f"(d[8]), "+f"(d[9]), "+f"(d[10]), "+f"(d[11]), "+f"(d[12]), "+f"(d[13]), "+f"(d[14]), "+f"(d[15]), "+f"(d[16]), "+f"(d[17]), "+f"(d[18]), "+f"(d[19])
    : "r"(a0), "r"(a1), "r"(a2), "r"(a3), "r"(db), "n"(TB), "n"(HI));
}
template<int TB, uint32_t HI> __device__ __forceinline__ void wgmma_rsz_n40(float (&d)[20], uint32_t a0, uint32_t a1, uint32_t a2, uint32_t a3, uint32_t db) {
  asm volatile("{\n.reg .pred p;\n.reg .b64 db;\nsetp.ne.b32 p, 0, 0;\nmov.b64 db, {%24, %26};\n"
    "wgmma.mma_async.sync.aligned.m64n40k16.f32.bf16.bf16 {%0, %1, %2, %3, %4, %5, %6, %7, %8, %9, %10, %11, %12, %13, %14, %15, %16, %17, %18, %19}, {%20, %21, %22, %23}, db, p, 1, 1, %25;\n}\n"
    : "=f"(d[0]), "=f"(d[1]), "=f"(d[2]), "=f"(d[3]), "=f"(d[4]), "=f"(d[5]), "=f"(d[6]), "=f"(d[7]), "=f"(d[8]), "=f"(d[9]), "=f"(d[10]), "=f"(d[11]), "=f"(d[12]), "=f"(d[13]), "=f"(d[14]), "=f"(d[15]), "=f"(d[16]), "=f"(d[17]), "=f"(d[18]), "=f"(d[19])
    : "r"(a0), "r"(a1), "r"(a2), "r"(a3), "r"(db), "n"(TB), "n"(HI));
}
template<int TB, uint32_t HI> __device__ __forceinline__ void wgmma_rs_n32(float (&d)[16], uint32_t a0, uint32_t a1, uint32_t a2, uint32_t a3, uint32_t db) {
  asm volatile("{\n.reg .pred p;\n.reg .b64 db;\nsetp.ne.b32 p, 1, 0;\nmov.b64 db, {%20, %22};\n"
    "wgmma.mma_async.sync.aligned.m64n32k16.f32.bf16.bf16 {%0, %1, %2, %3, %4, %5, %6, %7, %8, %9, %10, %11, %12, %13, %14, %15}, {%16, %17, %18, %19}, db, p, 1, 1, %21;\n}\n"
    : "+f"(d[0]), "+f"(d[1]), "+f"(d[2]), "+f"(d[3]), "+f"(d[4]), "+f"(d[5]), "+f"(d[6]), "+f"(d[7]), "+f"(d[8]), "+f"(d[9]), "+f"(d[10]), "+f"(d[11]), "+f"(d[12]), "+f"(d[13]), "+f"(d[14]), "+f"(d[15])
    : "r"(a0), "r"(a1), "r"(a2), "r"(a3), "r"(db), "n"(TB), "n"(HI));
}
template<int TB, uint32_t HI> __device__ __forceinline__ void wgmma_rsz_n32(float (&d)[16], uint32_t a0, uint32_t a1, uint32_t a2, uint32_t a3, uint32_t db) {
  asm volatile("{\n.reg .pred p;\n.reg .b64 db;\nsetp.ne.b32 p, 0, 0;\nmov.b64 db, {%20, %22};\n"
    "wgmma.mma_async.sync.aligned.m64n32k16.f32.bf16.bf16 {%0, %1, %2, %3, %4, %5, %6, %7, %8, %9, %10, %11, %12, %13, %14, %15}, {%16, %17, %18, %19}, db, p, 1, 1, %21;\n}\n"
    : "=f"(d[0]), "=f"(d[1]), "=f"(d[2]), "=f"(d[3]), "=f"(d[4]), "=f"(d[5]), "=f"(d[6]), "=f"(d[7]), "=f"(d[8]), "=f"(d[9]), "=f"(d[10]), "=f"(d[11]), "=f"(d[12]), "=f"(d[13]), "=f"(d[14]), "=f"(d[15])
    : "r"(a0), "r"(a1), "r"(a2), "r"(a3), "r"(db), "n"(TB), "n"(HI));
}

__device__ __forceinline__ void phi_mma(float (&d)[16], const uint32_t* a, uint32_t wphi) {
  wgmma_rsz_n32<1, H64>(d, a[0], a[1], a[2], a[3], desc_lo(wphi, 2048));
  wgmma_rs_n32<1, H64>(d, a[4], a[5], a[6], a[7], desc_lo(wphi + 1024, 2048));
}

constexpr int NJOBS = 7;
constexpr int NST = 16 * 6 + 56;
constexpr int J_Q = 16, J_WO = 32, J_F1 = 48, J_F1A = 64, J_F2 = 96;
struct Sched { int off[NST]; int need[NST]; };
constexpr int JSZ[NJOBS] = {6, 4, 4, 5, 4, 4, 4};
constexpr Sched make_sched() {
  Sched s{};
  int off = 0;
  for (int g = 0; g < NST; g++) {
    int j = g < J_F2 ? g / 16 : 6, sz = JSZ[j];
    if (off + sz > 24) off = 0;
    if ((j == 1 || g == J_WO) && off == 4) off = 8;
    s.off[g] = off;
    int need = g - 8;
    for (int p = g - 1; p >= 0 && p > g - 8; p--)
      if (s.off[p] < off + sz && off < s.off[p] + JSZ[p < J_F2 ? p / 16 : 6]) { need = p; break; }
    s.need[g] = need;
    off += sz;
  }
  return s;
}
constexpr Sched SCH = make_sched();
static_assert(SCH.off[J_WO] == 8 && SCH.off[J_WO + 3] == 20 && SCH.off[J_WO + 5] == 4 && SCH.off[J_F1] == 0 && SCH.off[J_F1 + 3] == 15 &&
              SCH.off[J_F1 + 4] == 0 && SCH.off[12] == 0 && SCH.off[13] == 6, "schedule");
constexpr int LAST_REL = SCH.need[NST - 1];
template<int G> constexpr uint32_t OFF = SCH.off[G] * 8192;
template<int G> constexpr int NEED = SCH.need[G];
struct Tab { uint32_t a[8][192][2]; uint32_t b[8][192]; };
constexpr Tab make_tab() {
  Tab t{};
  for (int n = 0; n < 8; n++)
    for (int g = 0; g < NST; g++) {
      const int j = g < J_F2 ? g / 16 : 6, i = g - j * 16, rank = n & 1;
      const bool own = j == 2 || j == 3;
      int k = i;
      if (own) {
        if (i < 4) k = 2 * (n ^ (i & 1)) + (i >> 1);
        else { int odd = i >= 10; k = 2 * (((n & 6) + 2 + i - 4 - odd * 6) & 7) + odd; }
      }
      const int tx = JSZ[j] - (own && (i == 0 || i == 2) ? 2 : 0);
      const bool ev = g == J_WO + 5 || g == J_F1 + 4;
      t.b[n][g] = SCH.off[g] | (g - SCH.need[g]) << 5 | tx << 9 | j << 12 | k << 15 | (j == 3 ? 3 * n : 2 * n) << 21 | (ev ? 1 : 0) << 26;
      int need = SCH.need[g], tile = k, line = 0; uint32_t want = 0;
      if (j == 1) { line = rank; want = 0xFu << ((i >> 1) * 4); }
      else if (own) {
        const int R = j == 2 ? 6 : 4; const uint32_t pm = 5u << ((n & 6) * 2);
        tile = (j - 1) * 16 + k; line = j; want = (1u << k) | (i >= R ? pm : 0u) | (i >= R + 2 ? pm * 2 : 0u);
        if (i == R && need < g - R + 1) need = g - R + 1;
        if (i == R + 2 && need < g - R + 1) need = g - R + 1;
      } else if (j == 6) {
        tile = 48 + i; line = 4 + rank + (i < 24 ? 0 : i < 40 ? 2 : 4); want = 0xFu << ((i < 24 ? i / 3 : ((i - 24) & 15) >> 1) * 4);
      } else if (j > 3) { tile = 32 + i; line = 3; }
      t.a[n][g][0] = want;
      t.a[n][g][1] = SCH.off[g] | (g - need) << 5 | tile << 9 | line << 16 | (own && i < 4 ? 1 : 0) << 20 | (g == J_WO + 5 ? 1 : 0) << 21;
    }
  return t;
}
__device__ const Tab g_tab = make_tab();

constexpr uint32_t SM_RING = 192 * 1024;
constexpr uint32_t SM_SCR = 32 * 1024;
constexpr uint32_t SM_MISC = SM_RING;
constexpr uint32_t SM_WPHI = SM_MISC;
constexpr uint32_t SM_STG = SM_MISC + 8192;
constexpr uint32_t SM_GS1 = SM_MISC + 24576;
constexpr uint32_t SM_GS2 = SM_MISC + 28672;
constexpr uint32_t SM_VEC = SM_MISC + 32768;
constexpr uint32_t SM_BAR = SM_MISC + 34816;
constexpr uint32_t SM_TOTAL = SM_MISC + 35840;
constexpr uint32_t B_FULL = SM_BAR, B_EMPTY = SM_BAR + 64, B_SCR = SM_BAR + 128, B_WPHI = SM_BAR + 136, B_VEC = SM_BAR + 144,
                   B_UT = SM_BAR + 152, B_GS1 = SM_BAR + 160, B_KV = SM_BAR + 168, B_T0 = SM_BAR + 176;
constexpr uint32_t SM_RED = SM_BAR + 256;

struct Params {
  CUtensorMap tm_b[NJOBS], tm_x, tm_out, tm_wphi;
  const bf16 *x, *wqkv, *wo, *w1, *w2, *b1, *b2, *c, *wmod;
};

__device__ __forceinline__ float silu_bf(float v) { return bf_round(__fdividef(v, 1.f + __expf(-v))); }
__device__ __forceinline__ void wait_empty(uint32_t sb, int g) { mbar_wait(sb + B_EMPTY + 8 * (g & 7), (g >> 3) & 1); }

template<int SZ, bool SKIP> __device__ __forceinline__ uint32_t next_slot(uint32_t a, uint32_t sb) {
  a += SZ * 8192;
  if (a == sb + (24 / SZ) * SZ * 8192) a = sb;
  if (SKIP && a == sb + SM_SCR) a += 32768;
  return a;
}

struct Ctx { uint32_t sb, ebase, stg, srow; int wg, tid, lane, w4; uint32_t epoch; };
struct Pipe { uint32_t g, a; };

__device__ __forceinline__ void release_stage(const Ctx& c, uint32_t g) { if (c.tid < 2) mbar_arrive_cl(c.ebase + 8 * (g & 7)); }
__device__ __forceinline__ void wait_full(const Ctx& c, const Pipe& p) { mbar_wait(c.sb + B_FULL + 8 * (p.g & 7), (p.g >> 3) & 1); }
template<int N, int Z> __device__ __forceinline__ void mma4(const Ctx& c, float (&acc)[N / 2], const Pipe& p, uint32_t sd = 1) {
  uint32_t da = desc_lo(p.a + c.wg * 8192, 0), db = desc_lo(p.a + 16384, 8192);
#pragma unroll
  for (int k = 0; k < 4; k++) {
    if constexpr (N == 192) { if (Z && k == 0) wgmma_ssz_n192<0, 1, H128>(acc, da, db); else wgmma_ss_n192<0, 1, H128>(acc, da + k * 2, db + k * 128); }
    else { if (Z && k == 0) wgmma_ssp_n128<0, 1, H128>(acc, da, db, sd); else wgmma_ss_n128<0, 1, H128>(acc, da + k * 2, db + k * 128); }
  }
}
template<int N, bool SKIP> __device__ __forceinline__ void step(const Ctx& c, Pipe& p, float (&acc)[N / 2]) {
  wait_full(c, p);
  wgmma_fence();
  mma4<N, 0>(c, acc, p);
  wgmma_commit();
  wgmma_wait<1>();
  release_stage(c, p.g - 1);
  p.g++; p.a = next_slot<N == 192 ? 5 : 4, SKIP>(p.a, c.sb);
}

__device__ __forceinline__ void dual_softmax(const float* p, uint32_t (&ph)[16]) {
  constexpr float L2E = 1.4426950408889634f;
#pragma unroll
  for (int r = 0; r < 2; r++) {
    float mx = fmaxf(p[2 * r], p[2 * r + 1]), mn = fminf(p[2 * r], p[2 * r + 1]);
#pragma unroll
    for (int j = 1; j < 4; j++) { mx = fmaxf(mx, fmaxf(p[4 * j + 2 * r], p[4 * j + 2 * r + 1])); mn = fminf(mn, fminf(p[4 * j + 2 * r], p[4 * j + 2 * r + 1])); }
    mx = fmaxf(mx, __shfl_xor_sync(~0u, mx, 1)); mn = fminf(mn, __shfl_xor_sync(~0u, mn, 1));
    mx = fmaxf(mx, __shfl_xor_sync(~0u, mx, 2)); mn = fminf(mn, __shfl_xor_sync(~0u, mn, 2));
    float a = -mx * L2E, b = mn * L2E;
    float ep[8], en[8], sp = 0.f, sn = 0.f;
#pragma unroll
    for (int j = 0; j < 4; j++)
#pragma unroll
      for (int e = 0; e < 2; e++) {
        float v = p[4 * j + 2 * r + e];
        ep[2 * j + e] = ex2(fmaf(v, L2E, a)); en[2 * j + e] = ex2(fmaf(v, -L2E, b));
        sp += ep[2 * j + e]; sn += en[2 * j + e];
      }
    sp += __shfl_xor_sync(~0u, sp, 1); sn += __shfl_xor_sync(~0u, sn, 1);
    sp += __shfl_xor_sync(~0u, sp, 2); sn += __shfl_xor_sync(~0u, sn, 2);
    float ip = rcp(sp), in = rcp(sn);
#pragma unroll
    for (int j = 0; j < 4; j++) {
      ph[2 * j + r] = pack_bf16(ep[2 * j] * ip, ep[2 * j + 1] * ip);
      ph[8 + 2 * j + r] = pack_bf16(en[2 * j] * in, en[2 * j + 1] * in);
    }
  }
}
__device__ __forceinline__ void row_stats(const uint32_t (&v)[32], int lane, float& s0, float& s1, float& q0, float& q1) {
  float ds[4] = {0.f, 0.f, 0.f, 0.f}, d0[4] = {0.f, 0.f, 0.f, 0.f}, d1[4] = {0.f, 0.f, 0.f, 0.f};
#pragma unroll
  for (int k = 0; k < 8; k++) {
    hmma(ds, v[4 * k], v[4 * k + 1], v[4 * k + 2], v[4 * k + 3], 0x3f803f80u, 0x3f803f80u);
    hmma(d0, v[4 * k], v[4 * k + 1], v[4 * k + 2], v[4 * k + 3], v[4 * k], v[4 * k + 2]);
    hmma(d1, v[4 * k], v[4 * k + 1], v[4 * k + 2], v[4 * k + 3], v[4 * k + 1], v[4 * k + 3]);
  }
  s0 = ds[0]; s1 = ds[2]; q0 = (lane & 4) ? d0[1] : d0[0]; q1 = (lane & 4) ? d1[3] : d1[2];
}

__device__ __forceinline__ uint32_t stm_addr(const Ctx& c, uint32_t base, int cb) { return base + (c.srow ^ (cb << 4)); }

__device__ __forceinline__ void stg_acquire(const Ctx& c) { if (c.lane == 0) bulk_wait_read0(); __syncwarp(); }
__device__ __forceinline__ void stg_store(const Ctx& c, uint8_t* dst) {
  fence_async_smem();
  __syncwarp();
  if (c.lane == 0) { bulk_store(dst, c.stg, 2048); bulk_commit(); }
}
__device__ __forceinline__ void warp_publish(const Ctx& c, uint32_t* flag) { if (c.lane == 0) { bulk_wait0(); st_relaxed(flag, c.epoch); } __syncwarp(); }

__device__ __forceinline__ uint4 poll4(const void* p, uint32_t epoch) {
  uint4 v; uint32_t n = 0;
  do { v = ld_vol4(p); spin_guard(++n); } while (v.y != epoch || v.w != epoch);
  return v;
}
__device__ __forceinline__ void poll4x2(const void* p0, const void* p1, uint32_t epoch, uint4& v, uint4& w) {
  uint32_t n = 0;
  do { v = ld_vol4(p0); w = ld_vol4(p1); spin_guard(++n); } while (v.y != epoch || v.w != epoch || w.y != epoch || w.w != epoch);
}
__device__ __forceinline__ void poll_flags(const uint32_t* flags, int lane, uint32_t epoch, uint32_t want, uint32_t& mask) {
  uint32_t it = 0;
  while ((mask & want) != want) {
    mask = __ballot_sync(~0u, ld_relaxed(flags + lane) == epoch);
    spin_guard(++it);
  }
}

__global__ void __cluster_dims__(2, 1, 1) __launch_bounds__(384, 1) mega_kernel(const __grid_constant__ Params p) {
  extern __shared__ __align__(1024) uint8_t smem_raw[];
  uint32_t sb = smem_u32(smem_raw);
  asm volatile("" : "+r"(sb));
  const int tid = threadIdx.x, lane = tid & 31, warp = __shfl_sync(~0u, tid >> 5, 0), wg = warp >> 2;
  const int b = blockIdx.x, m = b >> 3, n = b & 7, rank = b & 1;
  uint8_t* const act = g_act + (size_t)m * 104 * 16384;
  uint32_t* const flg = g_flag + m * 320;

  if (wg == 2) {
    if (warp == 8) {
      if (lane == 0) { TL(0); spin_guard((sb & 1023) ? ~0u : 0u); }
      if (lane < 24) mbar_init(sb + SM_BAR + 8 * lane, lane < 8 ? 1u : lane < 16 ? 4u : 1u << ((0x11336602u >> (4 * (lane - 16))) & 15));
      asm volatile("fence.mbarrier_init.release.cluster;" ::: "memory");
    }
    if (tid == 288) { prefetch_tmap(&p.tm_x); prefetch_tmap(&p.tm_b[0]); prefetch_tmap(&p.tm_wphi); }
    __syncwarp();
    cluster_arrive();
    const uint32_t epoch = ld_relaxed(&g_epoch) + 1;
    reg_dealloc<56>();
    if (warp == 8) {
      uint32_t rec = 0, nxt = ld_nc1(&g_tab.b[n][lane]);
      const uint32_t peer = mapa(sb, rank ^ 1);
      cluster_wait();
#pragma unroll 1
      for (int g = 0; g < NST; g++) {
        if (!(g & 31)) { rec = nxt; nxt = ld_nc1(&g_tab.b[n][g + 32 + lane]); }
        const uint32_t w = __shfl_sync(~0u, rec, g);
        if (lane == 0) {
          const uint32_t f1 = g >= J_F1;
          if (w >> 26) {
#pragma unroll 1
            for (uint32_t t = 0; t < 2; t++) {
              const uint32_t src = f1 ? t * 81920 : 65536 + t * 65536;
              mbar_wait(sb + B_T0 + 8 * t, f1);
              bulk_store(act + (16 + 16 * f1 + 2 * n + t) * 16384, sb + src, 16384); bulk_commit();
              bulk_copy_peer(peer + src + 32768 + f1 * 8192, sb + src, 16384, peer + B_FULL + 8 + 16 * t);
              if (t == 0) { bulk_wait0(); st_relaxed(flg + 64 + 32 * f1 + 2 * n, epoch); TL(40 + 2 * f1); }
            }
            mbar_wait(sb + B_SCR, 0);
          }
          wait_empty(sb, g - (int)((w >> 5) & 15));
          const uint32_t bar = sb + B_FULL + 8 * (g & 7);
          mbar_expect_tx(bar, ((w >> 9) & 7) * 8192);
          tma_load_4d(sb + (w & 31) * 8192 + 16384, &p.tm_b[(w >> 12) & 7], bar, ((w >> 15) & 63) * 64, (w >> 21) & 31);
          if (w >> 26) { bulk_wait0(); st_relaxed(flg + 64 + 32 * f1 + 2 * n + 1, epoch); TL(41 + 2 * f1); }
          if (g == 3) { mbar_expect_tx(sb + B_WPHI, 8192); tma_load_2d(sb + SM_WPHI, &p.tm_wphi, sb + B_WPHI, 0, n * 128); }
        }
        __syncwarp();
      }
    } else if (warp == 9) {
      uint2 rec = {0u, 0u}, nxt = ld_nc2(&g_tab.a[n][lane][0]);
      uint32_t mask = 0, line = 0;
      cluster_wait();
#pragma unroll 1
      for (int g = 0; g < NST; g++) {
        if (!(g & 31)) { rec = nxt; nxt = ld_nc2(&g_tab.a[n][g + 32 + lane][0]); }
        const uint32_t want = __shfl_sync(~0u, rec.x, g), w = __shfl_sync(~0u, rec.y, g);
        if (w & (1u << 20)) continue;
        if (((w >> 16) & 15) != line) { line = (w >> 16) & 15; mask = 0; }
        poll_flags(flg + line * 32, lane, epoch, want, mask);
        wait_empty(sb, g - (int)((w >> 5) & 15));
        if (w >> 21) mbar_wait(sb + B_SCR, 0);
        if (lane == 0) {
          const uint32_t bar = sb + B_FULL + 8 * (g & 7), dst = sb + (w & 31) * 8192 + rank * 8192;
          if (g < 16) tma_load_2d_mc(dst, &p.tm_x, bar, g * 64, m * 128 + rank * 64, 3);
          else bulk_load_mc(dst, act + ((w >> 9) & 127) * 16384 + rank * 8192, 8192, bar);
        }
        __syncwarp();
      }
    } else {
      const int ht = tid - 320;
#pragma unroll 1
      for (int i = ht; i < 160; i += 64) g_kvacc[(epoch + 1) & 1][b * 160 + i] = make_float4(0.f, 0.f, 0.f, 0.f);
#pragma unroll 1
      for (int i = ht; i < 512; i += 64) {
        uint32_t cv = ld_nc1(p.c + 2 * i);
        sts2(sb + SM_GS2 + i * 8, pack_bf16(silu_bf(bf_lo(cv)), 0.f), pack_bf16(silu_bf(bf_hi(cv)), 0.f));
      }
      cluster_wait();
      mbar_wait(sb + B_GS1, 0);
      if (ht < 8) bulk_prefetch(p.wmod + (size_t)(b * 8 + ht) * 6144 + 2048, 8192);
      else if (ht < 16) bulk_prefetch(p.wqkv + (size_t)(b * 8 + ht - 8) * 3072, 6144);
      else if (ht == 32) bulk_prefetch(p.wo + (size_t)b * 8192, 16384);
      else if (ht >= 40 && ht < 48) bulk_prefetch(p.w1 + (size_t)(b * 8 + ht - 40) * FF, FF * 2);
#pragma unroll 1
      for (int pass = 0; pass < 2; pass++) {
        bar_sync(4, 64);
        if (pass == 0 || b < 112) {
          const int ld = pass ? FF : 6144;
          const bf16* wp = (pass ? p.w1 : p.wmod + 2048) + b * 32 + (ht >> 3) * ld + (ht & 7) * 4;
          float a[8];
#pragma unroll
          for (int e = 0; e < 8; e++) a[e] = 0.f;
#pragma unroll 1
          for (int it = 0; it < 8; it++) {
            uint2 v[16];
#pragma unroll
            for (int u = 0; u < 16; u++) { v[u] = ld_nc2(wp); wp += 8 * ld; }
#pragma unroll
            for (int u = 0; u < 16; u++) {
              uint32_t cf = lds1(sb + SM_GS2 + ((it * 16 + u) * 8 + (ht >> 3)) * 4);
              float c0 = bf_lo(cf), c1 = bf_hi(cf), w0 = bf_lo(v[u].x), w1 = bf_hi(v[u].x), w2 = bf_lo(v[u].y), w3 = bf_hi(v[u].y);
              a[0] = fmaf(c0, w0, a[0]); a[2] = fmaf(c0, w1, a[2]); a[4] = fmaf(c0, w2, a[4]); a[6] = fmaf(c0, w3, a[6]);
              a[1] = fmaf(c1, w0, a[1]); a[3] = fmaf(c1, w1, a[3]); a[5] = fmaf(c1, w2, a[5]); a[7] = fmaf(c1, w3, a[7]);
            }
          }
#pragma unroll
          for (int e = 0; e < 8; e++) { a[e] += __shfl_xor_sync(~0u, a[e], 8); a[e] += __shfl_xor_sync(~0u, a[e], 16); }
          if (lane < 8) {
            sts4(sb + SM_RED + (ht >> 5) * 256 + lane * 32, __float_as_uint(a[0]), __float_as_uint(a[1]), __float_as_uint(a[2]), __float_as_uint(a[3]));
            sts4(sb + SM_RED + (ht >> 5) * 256 + lane * 32 + 16, __float_as_uint(a[4]), __float_as_uint(a[5]), __float_as_uint(a[6]), __float_as_uint(a[7]));
          }
          bar_sync(4, 64);
          uint2 x0 = lds2(sb + SM_RED + lane * 8), x1 = lds2(sb + SM_RED + 256 + lane * 8);
          float o0 = __uint_as_float(x0.x) + __uint_as_float(x1.x), o1 = __uint_as_float(x0.y) + __uint_as_float(x1.y);
          float nb = __shfl_down_sync(~0u, o0, 1);
          if (ht < 32) {
            if (pass) st_vol4(&g_utpk[b * 32 + ht], __float_as_uint(o0), epoch, __float_as_uint(o1 + __bfloat162float(p.b1[b * 32 + ht])), epoch);
            else if (!(ht & 1)) st_vol2(&g_modpk[1024 + b * 16 + (ht >> 1)], pack_bf16(o0, nb), epoch);
          }
        }
        if (ht == 0) TL(48 + 2 * pass);
        if (pass) break;
        if (ht < 8) bulk_prefetch(p.w2 + (size_t)(b * 8 + ht) * FF, FF * 2);
#pragma unroll 1
        for (int i = ht; i < 256; i += 64) {
          uint4 s, cc;
          poll4x2(&g_modpk[1536 + 2 * i], &g_modpk[2048 + 2 * i], epoch, s, cc);
          sts4(sb + SM_GS2 + i * 16, pack_bf16(1.f + bf_lo(cc.x), bf_lo(s.x)), pack_bf16(1.f + bf_hi(cc.x), bf_hi(s.x)),
               pack_bf16(1.f + bf_lo(cc.z), bf_lo(s.z)), pack_bf16(1.f + bf_hi(cc.z), bf_hi(s.z)));
          if ((i >> 5) == n) { sts1(sb + SM_VEC + lane * 32 + 4, pack_bf16(1.f + bf_lo(cc.x), 1.f + bf_hi(cc.x))); sts1(sb + SM_VEC + lane * 32 + 20, pack_bf16(1.f + bf_lo(cc.z), 1.f + bf_hi(cc.z))); }
        }
        {
          uint4 gv = poll4(&g_modpk[1024 + (ht >> 5) * 1536 + n * 64 + lane * 2], epoch);
          sts1(sb + SM_VEC + lane * 32 + (ht >> 5) * 8, gv.x); sts1(sb + SM_VEC + lane * 32 + 16 + (ht >> 5) * 8, gv.z);
          sts1(sb + SM_VEC + ht * 16 + 12, ld_nc1(p.b2 + n * 128 + 2 * ht));
        }
        mbar_arrive(sb + B_VEC);
        if (ht == 0) {
          TL(49);
          mbar_wait(sb + B_KV, 0);
          TL(52);
          __threadfence();
          st_relaxed(&g_kvflag[n * 32 + m], epoch);
          TL(53);
        }
      }
      mbar_wait(sb + B_SCR, 0);
      if (ht == 0) { uint32_t t = atomicInc(&g_done, 127); if (t == 127) g_epoch = epoch; }
#pragma unroll 1
      for (int i = ht; i < 448; i += 64) {
        int col = i < 192 ? n * 192 + i : n * 128 + 1344 + i + (i < 320 ? 0 : 896);
        uint4 v = poll4(&g_utpk[col], epoch);
        sts2(sb + SM_WPHI + i * 8, v.x, v.z);
      }
      mbar_arrive(sb + B_UT);
      if (ht == 0) TL(51);
    }
  } else {
    const int q = lane & 3;
    const int r0 = m * 128 + wg * 64 + (warp & 3) * 16 + (lane >> 2);
    Ctx c;
    float rs0, nm0, rs1, nm1;
    {
      uint4 wv[8];
      uint32_t xv[32];
      uint16_t cv[8];
      const bf16* wp = p.wmod + (size_t)(tid >> 1) * 6144 + b * 16 + (tid & 1) * 8;
#pragma unroll
      for (int i = 0; i < 8; i++) wv[i] = ld_nc4p(wp + (size_t)i * 128 * 6144);
#pragma unroll
      for (int i = 0; i < 8; i++) asm volatile("ld.global.nc.u16 %0, [%1];" : "=h"(cv[i]) : "l"(p.c + (tid >> 1) + i * 128));
      const uint32_t epoch = ld_relaxed(&g_epoch) + 1;
#pragma unroll
      for (int i = 0; i < 8; i++) {
        uint4 v = ld_nc4(p.x + (size_t)(b * 16 + (lane >> 2) + (i & 1) * 8) * DM + warp * 128 + (i >> 1) * 32 + q * 8);
        xv[(i >> 1) * 8 + (i & 1)] = v.x; xv[(i >> 1) * 8 + (i & 1) + 2] = v.y; xv[(i >> 1) * 8 + (i & 1) + 4] = v.z; xv[(i >> 1) * 8 + (i & 1) + 6] = v.w;
      }
      cluster_arrive();
      reg_alloc<224>();
      c.sb = sb; c.wg = wg; c.tid = tid & 127; c.lane = lane; c.w4 = warp & 3; c.epoch = epoch;
      c.ebase = mapa(sb + B_EMPTY, tid & 1); c.stg = sb + SM_STG + warp * 2048;
      c.srow = (lane & 15) * 128 + (((lane >> 4) ^ (lane & 7)) << 4);
      float a[8];
#pragma unroll
      for (int e = 0; e < 8; e++) a[e] = 0.f;
#pragma unroll
      for (int i = 0; i < 8; i++) {
        float cf = silu_bf(bf_lo(cv[i]));
        uint32_t vv[4] = {wv[i].x, wv[i].y, wv[i].z, wv[i].w};
#pragma unroll
        for (int e = 0; e < 4; e++) { a[2 * e] = fmaf(cf, bf_lo(vv[e]), a[2 * e]); a[2 * e + 1] = fmaf(cf, bf_hi(vv[e]), a[2 * e + 1]); }
      }
#pragma unroll
      for (int e = 0; e < 4; e++) { bool up = lane & 8; float s = up ? a[e] : a[e + 4], k = up ? a[e + 4] : a[e]; a[e] = k + __shfl_xor_sync(~0u, s, 8); }
#pragma unroll
      for (int e = 0; e < 2; e++) { bool up = lane & 4; float s = up ? a[e] : a[e + 2], k = up ? a[e + 2] : a[e]; a[e] = k + __shfl_xor_sync(~0u, s, 4); }
      { bool up = lane & 2; float s = up ? a[0] : a[1], k = up ? a[1] : a[0]; a[0] = k + __shfl_xor_sync(~0u, s, 2); }
      a[0] += __shfl_xor_sync(~0u, a[0], 16);
      if (lane < 16) sts1(c.stg + ((lane & 1) * 8 + (lane >> 1)) * 4, __float_as_uint(a[0]));
      float s0, s1, q0, q1;
      row_stats(xv, lane, s0, s1, q0, q1);
      if (q == (lane >> 3)) { sts2(c.stg + 64 + (lane >> 2) * 8, __float_as_uint(s0), __float_as_uint(q0)); sts2(c.stg + 128 + (lane >> 2) * 8, __float_as_uint(s1), __float_as_uint(q1)); }
      bar_sync(3, 256);
      if (tid < 24) {
        s0 = 0.f; s1 = 0.f;
#pragma unroll
        for (int w = 0; w < 8; w++) { uint2 v = lds2(sb + SM_STG + w * 2048 + tid * 8); s0 += __uint_as_float(v.x); s1 += __uint_as_float(v.y); }
        if (tid < 8) st_vol2(&g_modpk[b * 8 + tid], pack_bf16(s0, s1), epoch);
        else {
          s0 *= (1.f / DM);
          float rs = rsqrtf(fmaxf(fmaf(s1, 1.f / DM, -s0 * s0), 0.f) + 1e-5f);
          st_vol4(&g_st1pk[b * 16 + tid - 8], __float_as_uint(rs), epoch, __float_as_uint(-s0 * rs), epoch);
        }
      }
      if (tid == 0) TL(1);
      cluster_wait();
      if (lane == 0) mbar_arrive(sb + B_GS1);
      {
        uint4 sv, cc;
        poll4x2(&g_modpk[2 * tid], &g_modpk[512 + 2 * tid], epoch, sv, cc);
        uint32_t ad = sb + SM_GS1 + (tid >> 2) * 64 + (tid & 1) * 32 + ((tid >> 1) & 1) * 4;
        sts1(ad, pack_bf16(1.f + bf_lo(cc.x), 1.f + bf_hi(cc.x))); sts1(ad + 8, sv.x);
        sts1(ad + 16, pack_bf16(1.f + bf_lo(cc.z), 1.f + bf_hi(cc.z))); sts1(ad + 24, sv.z);
        poll4x2(&g_st1pk[r0], &g_st1pk[r0 + 8], epoch, sv, cc);
        rs0 = __uint_as_float(sv.x); nm0 = __uint_as_float(sv.z); rs1 = __uint_as_float(cc.x); nm1 = __uint_as_float(cc.z);
      }
      bar_sync(3, 256);
      if (tid == 0) TL(2);
    }
    const uint32_t epoch = c.epoch;
    const uint32_t wrow = wg * 8192 + c.w4 * 2048;
    uint32_t* const wflag = flg + wg * 32 + n * 4 + c.w4;
    Pipe pp;
    float accq[64];
    {
      float acc[128];
      uint32_t A[16];
      zero_regs(acc);
      pp.g = 0; pp.a = sb;
#pragma unroll 1
      do {
        uint32_t T[16];
        wait_full(c, pp);
#pragma unroll
        for (int k = 0; k < 4; k++) {
          ldmatrix_x4(stm_addr(c, pp.a + wrow, 2 * k), T[4 * k], T[4 * k + 1], T[4 * k + 2], T[4 * k + 3]);
          T[4 * k] = pack_bf16(fmaf(bf_lo(T[4 * k]), rs0, nm0), fmaf(bf_hi(T[4 * k]), rs0, nm0));
          T[4 * k + 1] = pack_bf16(fmaf(bf_lo(T[4 * k + 1]), rs1, nm1), fmaf(bf_hi(T[4 * k + 1]), rs1, nm1));
          T[4 * k + 2] = pack_bf16(fmaf(bf_lo(T[4 * k + 2]), rs0, nm0), fmaf(bf_hi(T[4 * k + 2]), rs0, nm0));
          T[4 * k + 3] = pack_bf16(fmaf(bf_lo(T[4 * k + 3]), rs1, nm1), fmaf(bf_hi(T[4 * k + 3]), rs1, nm1));
        }
        uint4 gs[4];
#pragma unroll
        for (int k = 0; k < 4; k++) gs[k] = lds4(sb + SM_GS1 + (pp.g * 4 + k) * 64 + q * 16);
        wgmma_wait<0>();
#pragma unroll
        for (int k = 0; k < 4; k++) {
          asm volatile("fma.rn.bf16x2 %0, %1, %2, %3;" : "=r"(A[4 * k]) : "r"(T[4 * k]), "r"(gs[k].x), "r"(gs[k].z));
          asm volatile("fma.rn.bf16x2 %0, %1, %2, %3;" : "=r"(A[4 * k + 1]) : "r"(T[4 * k + 1]), "r"(gs[k].x), "r"(gs[k].z));
          asm volatile("fma.rn.bf16x2 %0, %1, %2, %3;" : "=r"(A[4 * k + 2]) : "r"(T[4 * k + 2]), "r"(gs[k].y), "r"(gs[k].w));
          asm volatile("fma.rn.bf16x2 %0, %1, %2, %3;" : "=r"(A[4 * k + 3]) : "r"(T[4 * k + 3]), "r"(gs[k].y), "r"(gs[k].w));
        }
        uint32_t db = desc_lo(pp.a + 16384, 8192);
        wgmma_fence();
#pragma unroll
        for (int k = 0; k < 4; k++) wgmma_rs_n256<1, H128>(acc, A[4 * k], A[4 * k + 1], A[4 * k + 2], A[4 * k + 3], db + k * 128);
        wgmma_commit();
        if (pp.g) release_stage(c, pp.g - 1);
        if ((int)(pp.g >> 1) == n) {
          stg_acquire(c);
#pragma unroll
          for (int k = 0; k < 4; k++) stmatrix_x4(stm_addr(c, c.stg, 2 * k), A[4 * k], A[4 * k + 1], A[4 * k + 2], A[4 * k + 3]);
          stg_store(c, act + pp.g * 16384 + wrow);
        }
        if ((int)pp.g == min(2 * n + 2, 15)) warp_publish(c, wflag);
        pp.g++; pp.a = next_slot<6, false>(pp.a, sb);
      } while (pp.g < J_Q);
      wgmma_wait<0>();
      fence_regs(acc);
      if (tid == 0) TL(4);
      zero_regs(accq);
      pp.a = sb + OFF<J_Q>;
      uint32_t lim = J_Q + 1 + wg;
#pragma unroll 1
      while (true) {
#pragma unroll 1
        do step<128, true>(c, pp, accq); while (pp.g < lim);
        if (lim == J_WO) break;
        lim = J_WO;
        uint32_t kp[32], vp[32];
#pragma unroll
        for (int i = 0; i < 32; i++) { kp[i] = pack_bf16(acc[2 * i], acc[2 * i + 1]); vp[i] = pack_bf16(acc[64 + 2 * i], acc[64 + 2 * i + 1]); }
        const uint32_t phi_t = sb + SM_SCR + wg * 16384, v_t = phi_t + 8192;
        wait_empty(sb, 13);
        mbar_wait(sb + B_WPHI, 0);
        if (lane < 16) sts4(v_t + c.w4 * 2048 + lane * 128 + ((4 ^ (lane & 7)) << 4), 0x3f803f80u, 0x3f803f80u, 0x3f803f80u, 0x3f803f80u);
        float4* dst = &g_kvacc[epoch & 1][n * 4 * 640 + c.tid];
#pragma unroll 1
        for (int hh = 0; hh < 4; hh++) {
          float pk[16];
          wait_full(c, pp);
          wgmma_fence();
          phi_mma(pk, kp, sb + SM_WPHI + hh * 2048);
          wgmma_commit();
          mma4<128, 0>(c, accq, pp);
          wgmma_commit();
          wgmma_wait<1>();
          fence_regs(pk);
          release_stage(c, pp.g - 1);
          pp.g++; pp.a = next_slot<4, true>(pp.a, sb);
          uint32_t ph[16];
          dual_softmax(pk, ph);
          bar_sync(1 + wg, 128);
#pragma unroll
          for (int jj = 0; jj < 4; jj++) stmatrix_x4(stm_addr(c, phi_t + c.w4 * 2048, jj * 2), ph[4 * jj], ph[4 * jj + 1], ph[4 * jj + 2], ph[4 * jj + 3]);
#pragma unroll
          for (int jj = 0; jj < 2; jj++) stmatrix_x4(stm_addr(c, v_t + c.w4 * 2048, jj * 2), vp[4 * jj], vp[4 * jj + 1], vp[4 * jj + 2], vp[4 * jj + 3]);
          fence_async_smem();
          bar_sync(1 + wg, 128);
          float kv[20];
          wait_full(c, pp);
          wgmma_fence();
          wgmma_ssz_n40<1, 1, H128>(kv, desc_lo(phi_t, 8192), desc_lo(v_t, 8192));
#pragma unroll
          for (int s = 1; s < 4; s++)
            wgmma_ss_n40<1, 1, H128>(kv, desc_lo(phi_t + s * 2048, 8192), desc_lo(v_t + s * 2048, 8192));
          wgmma_commit();
          mma4<128, 0>(c, accq, pp);
          wgmma_commit();
#pragma unroll
          for (int i = 0; i < 24; i++) { kp[i] = kp[i + 8]; vp[i] = vp[i + 8]; }
          wgmma_wait<1>();
          fence_regs(kv);
          release_stage(c, pp.g - 1);
          pp.g++; pp.a = next_slot<4, true>(pp.a, sb);
#pragma unroll
          for (int j = 0; j < 5; j++) red_add4(dst + j * 128, kv[4 * j], kv[4 * j + 1], kv[4 * j + 2], kv[4 * j + 3]);
          dst += 640;
        }
        __syncwarp();
        if (lane == 0) mbar_arrive(sb + B_KV);
        if (tid == 0) TL(5);
      }
    }
    float accw[64];
    {
      {
        uint32_t mask = 0;
        poll_flags(g_kvflag + n * 32, lane, epoch, 0xFFFFu, mask);
      }
      if (tid == 0) TL(7);
      uint4 v[10];
      {
        const float4* src = &g_kvacc[epoch & 1][(n * 4 + wg * 2) * 640 + c.tid];
#pragma unroll
        for (int i = 0; i < 10; i++) v[i] = ld_vol4(src + i * 128);
      }
      wgmma_wait<0>();
      fence_regs(accq);
      release_stage(c, J_WO - 1);
      if (tid == 0) TL(6);
      float pq[4][16];
      {
        uint32_t qp[32];
#pragma unroll
        for (int i = 0; i < 32; i++) qp[i] = pack_bf16(accq[2 * i], accq[2 * i + 1]);
        wgmma_fence();
#pragma unroll
        for (int hh = 0; hh < 4; hh++) phi_mma(pq[hh], qp + hh * 8, sb + SM_WPHI + hh * 2048);
        wgmma_commit();
        int f = c.w4 * 16 + (lane >> 2);
#pragma unroll
        for (int i = 0; i < 10; i++) {
          uint32_t a = sb + SM_SCR + (wg * 2 + i / 5) * 8192 + f * 128 + (((i % 5) ^ (f & 7)) << 4) + q * 4;
          sts1(a, pack_bf16(__uint_as_float(v[i].x), __uint_as_float(v[i].y)));
          sts1(a + 1024, pack_bf16(__uint_as_float(v[i].z), __uint_as_float(v[i].w)));
        }
        fence_async_smem();
        wgmma_wait<0>();
#pragma unroll
        for (int hh = 0; hh < 4; hh++) fence_regs(pq[hh]);
      }
      zero_regs(accw);
      wait_empty(sb, NEED<J_WO + 2>);
      pp.a = sb + OFF<J_WO>;
#pragma unroll 1
      for (int hh = 0; hh < 4; hh++) {
        uint32_t ph[16];
        float nd[20];
        dual_softmax(pq[0], ph);
        if (hh == 0) bar_sync(3, 256);
        const uint32_t db = desc_lo(sb + SM_SCR + hh * 8192, 8192);
        wgmma_fence();
        wgmma_rsz_n40<1, H128>(nd, ph[0], ph[1], ph[2], ph[3], db);
#pragma unroll
        for (int s = 1; s < 4; s++) wgmma_rs_n40<1, H128>(nd, ph[4 * s], ph[4 * s + 1], ph[4 * s + 2], ph[4 * s + 3], db + s * 128);
        wgmma_commit();
#pragma unroll
        for (int i = 0; i < 16; i++) { pq[0][i] = pq[1][i]; pq[1][i] = pq[2][i]; pq[2][i] = pq[3][i]; }
        wgmma_wait<0>();
        fence_regs(nd);
        if (hh >= 2) release_stage(c, pp.g - 1);
        float i0 = rcp(nd[16] + 1e-6f), i1 = rcp(nd[18] + 1e-6f);
#pragma unroll
        for (int jj = 0; jj < 2; jj++)
          stmatrix_x4(stm_addr(c, sb + OFF<J_WO> + (hh & 2) * 32768 + wrow, (hh & 1) * 4 + jj * 2), pack_bf16(nd[8 * jj] * i0, nd[8 * jj + 1] * i0),
                      pack_bf16(nd[8 * jj + 2] * i1, nd[8 * jj + 3] * i1), pack_bf16(nd[8 * jj + 4] * i0, nd[8 * jj + 5] * i0), pack_bf16(nd[8 * jj + 6] * i1, nd[8 * jj + 7] * i1));
        if (hh & 1) {
          fence_async_smem();
          bar_sync(1 + wg, 128);
          if (c.tid == 0) mbar_arrive(sb + B_T0 + (hh & 2) * 4);
          if (hh == 3 && c.tid < 2) mbar_arrive_cl(c.ebase + (B_SCR - B_EMPTY));
          if (tid == 0) TL(hh == 1 ? 20 : 8);
        }
        if (hh) {
          wait_full(c, pp);
          wgmma_fence(); mma4<128, 0>(c, accw, pp); wgmma_commit();
          pp.g++; pp.a += 32768;
        }
      }
    }
    float prev[96];
    float mr0, mr1;
    {
      uint32_t xr[32];
#pragma unroll
      for (int j = 0; j < 16; j++) {
        xr[2 * j] = ld_nc1(p.x + (size_t)r0 * DM + n * 128 + j * 8 + q * 2);
        xr[2 * j + 1] = ld_nc1(p.x + (size_t)(r0 + 8) * DM + n * 128 + j * 8 + q * 2);
      }
#pragma unroll 1
      do step<128, false>(c, pp, accw); while (pp.g < J_F1);
      mbar_wait(sb + B_VEC, 0);
      wait_empty(sb, NEED<J_F1 + 2>);
      wgmma_wait<0>();
      fence_regs(accw);
      release_stage(c, J_F1 - 1);
      if (tid == 0) TL(9);
#pragma unroll
      for (int pc = 0; pc < 2; pc++) {
#pragma unroll
        for (int jj = 0; jj < 4; jj++) {
          uint32_t r[4];
#pragma unroll
          for (int e = 0; e < 2; e++) {
            int j = pc * 8 + jj * 2 + e;
            uint2 gv = lds2(sb + SM_VEC + (j * 4 + q) * 16);
            float ga0 = bf_lo(gv.x), ga1 = bf_hi(gv.x);
            xr[2 * j] = pack_bf16(fmaf(ga0, accw[4 * j], bf_lo(xr[2 * j])), fmaf(ga1, accw[4 * j + 1], bf_hi(xr[2 * j])));
            xr[2 * j + 1] = pack_bf16(fmaf(ga0, accw[4 * j + 2], bf_lo(xr[2 * j + 1])), fmaf(ga1, accw[4 * j + 3], bf_hi(xr[2 * j + 1])));
            r[2 * e] = hmul2(xr[2 * j], gv.y); r[2 * e + 1] = hmul2(xr[2 * j + 1], gv.y);
          }
          stmatrix_x4(stm_addr(c, sb + (pc ? OFF<J_F1 + 2> : OFF<J_F1>) + wrow, jj * 2), r[0], r[1], r[2], r[3]);
        }
        fence_async_smem();
        bar_sync(1 + wg, 128);
        if (c.tid == 0) mbar_arrive(sb + B_T0 + pc * 8);
        if (pc == 0) {
          wait_full(c, pp);
          wgmma_fence(); mma4<192, 1>(c, prev, pp); wgmma_commit();
          pp.g++; pp.a += 40960;
        }
      }
      if (tid == 0) TL(10);
      {
        float s0, s1, q0, q1;
        row_stats(xr, lane, s0, s1, q0, q1);
        if (q == (lane >> 3)) {
          st_vol4(&g_st2pk[r0 * 8 + n], __float_as_uint(s0), epoch, __float_as_uint(q0), epoch);
          st_vol4(&g_st2pk[(r0 + 8) * 8 + n], __float_as_uint(s1), epoch, __float_as_uint(q1), epoch);
        }
      }
#pragma unroll
      for (int i = 0; i < 8; i++) g_x1f[(b * 8 + i) * 256 + tid] = make_uint4(xr[4 * i], xr[4 * i + 1], xr[4 * i + 2], xr[4 * i + 3]);
#pragma unroll 1
      do step<192, false>(c, pp, prev); while (pp.g < J_F1A);
      uint4 a0, a1, b0, b1;
      poll4x2(&g_st2pk[r0 * 8 + q * 2], &g_st2pk[r0 * 8 + q * 2 + 1], epoch, a0, a1);
      poll4x2(&g_st2pk[(r0 + 8) * 8 + q * 2], &g_st2pk[(r0 + 8) * 8 + q * 2 + 1], epoch, b0, b1);
      float s0 = __uint_as_float(a0.x) + __uint_as_float(a1.x), s1 = __uint_as_float(b0.x) + __uint_as_float(b1.x);
      float q0 = __uint_as_float(a0.z) + __uint_as_float(a1.z), q1 = __uint_as_float(b0.z) + __uint_as_float(b1.z);
#pragma unroll
      for (int o = 1; o < 4; o <<= 1) {
        s0 += __shfl_xor_sync(~0u, s0, o); s1 += __shfl_xor_sync(~0u, s1, o); q0 += __shfl_xor_sync(~0u, q0, o); q1 += __shfl_xor_sync(~0u, q1, o);
      }
      s0 *= (1.f / DM); s1 *= (1.f / DM);
      rs0 = rsqrtf(fmaxf(fmaf(q0, 1.f / DM, -s0 * s0), 0.f) + 1e-5f); rs1 = rsqrtf(fmaxf(fmaf(q1, 1.f / DM, -s1 * s1), 0.f) + 1e-5f);
      mr0 = -s0 * rs0; mr1 = -s1 * rs1;
    }
    float acc[64];
      zero_regs(acc);
    wgmma_wait<0>();
    fence_regs(prev);
    if (tid == 0) TL(11);
    {
      pp.a = sb + OFF<J_F1A>;
      uint32_t ut = sb + SM_WPHI + q * 16, pend = J_F1A + 7, job = 0;
      uint8_t* hid = act + (48 + 3 * n) * 16384 + wrow;
#pragma unroll 1
      while (true) {
        wait_full(c, pp);
        wgmma_fence();
        mma4<128, 2>(c, acc, pp, pp.g != J_F1A + 16 * job);
        wgmma_commit();
        wgmma_wait<1>();
        if (pp.g <= LAST_REL + 1) release_stage(c, pp.g - 1);
        pp.g++; pp.a = next_slot<4, false>(pp.a, sb);
        if (pp.g < pend) {
          mbar_wait(sb + B_UT, 0);
          if (pp.g & 1) stg_acquire(c);
#pragma unroll
          for (int jj = 0; jj < 2; jj++) {
            uint32_t r[4];
#pragma unroll
            for (int e = 0; e < 2; e++) {
              int j = jj * 2 + e;
              uint4 uv = lds4(ut + j * 64);
              float u0 = __uint_as_float(uv.x), t0 = __uint_as_float(uv.y), u1 = __uint_as_float(uv.z), t1 = __uint_as_float(uv.w);
              float z0 = fmaf(rs0, prev[4 * j], fmaf(mr0, u0, t0)), z1 = fmaf(rs0, prev[4 * j + 1], fmaf(mr0, u1, t1));
              float z2 = fmaf(rs1, prev[4 * j + 2], fmaf(mr1, u0, t0)), z3 = fmaf(rs1, prev[4 * j + 3], fmaf(mr1, u1, t1));
              r[2 * e] = pack_relu(z0 * fabsf(z0), z1 * fabsf(z1)); r[2 * e + 1] = pack_relu(z2 * fabsf(z2), z3 * fabsf(z3));
            }
            stmatrix_x4(stm_addr(c, c.stg, (~pp.g & 1) * 4 + jj * 2), r[0], r[1], r[2], r[3]);
          }
          if (!(pp.g & 1)) { stg_store(c, hid); hid += 16384; }
          ut += 256;
#pragma unroll
          for (int i = 0; i < 80; i++) prev[i] = prev[i + 16];
        } else if (pp.g == pend + 2) {
          warp_publish(c, wflag + 128 + 64 * job);
        } else if (pp.g == NST - 4) {
#pragma unroll
          for (int i = 0; i < 8; i++) {
            uint4 v = g_x1f[(b * 8 + i) * 256 + tid];
            prev[4 * i] = __uint_as_float(v.x); prev[4 * i + 1] = __uint_as_float(v.y); prev[4 * i + 2] = __uint_as_float(v.z); prev[4 * i + 3] = __uint_as_float(v.w);
          }
        } else if (pp.g == (job == 2 ? NST : J_F1A + 16 + 16 * job)) {
          wgmma_wait<0>();
          fence_regs(acc);
          if (tid == 0) TL(13 + 2 * job);
          if (job == 2) break;
#pragma unroll
          for (int i = 0; i < 64; i++) prev[i] = acc[i];
          hid = act + (72 + 16 * job + 2 * n) * 16384 + wrow;
          job++; pend = pp.g + 5;
        }
      }
    }
#pragma unroll
    for (int pc = 0; pc < 2; pc++) {
      const uint32_t ob = sb + pc * 32768 + wrow;
#pragma unroll
      for (int jj = 0; jj < 4; jj++) {
        uint32_t r[4];
#pragma unroll
        for (int e = 0; e < 2; e++) {
          int j = pc * 8 + jj * 2 + e;
          uint2 gv = lds2(sb + SM_VEC + (j * 4 + q) * 16 + 8);
          float gb0 = bf_lo(gv.x), gb1 = bf_hi(gv.x), b20 = bf_lo(gv.y), b21 = bf_hi(gv.y);
          uint32_t x0 = __float_as_uint(prev[2 * j]), x1 = __float_as_uint(prev[2 * j + 1]);
          r[2 * e] = pack_bf16(fmaf(gb0, acc[4 * j] + b20, bf_lo(x0)), fmaf(gb1, acc[4 * j + 1] + b21, bf_hi(x0)));
          r[2 * e + 1] = pack_bf16(fmaf(gb0, acc[4 * j + 2] + b20, bf_lo(x1)), fmaf(gb1, acc[4 * j + 3] + b21, bf_hi(x1)));
        }
        stmatrix_x4(stm_addr(c, ob, jj * 2), r[0], r[1], r[2], r[3]);
      }
      fence_async_smem();
      __syncwarp();
      if (lane == 0) { tma_store_2d(&p.tm_out, ob, n * 128 + pc * 64, m * 128 + wg * 64 + c.w4 * 16); bulk_commit(); }
    }
    if (lane == 0) bulk_wait_read0();
    if (tid == 0) TL(18);
  }
}

typedef CUresult (*PFN_encodeTiled)(CUtensorMap*, CUtensorMapDataType, cuuint32_t, void*, const cuuint64_t*, const cuuint64_t*, const cuuint32_t*,
                                    const cuuint32_t*, CUtensorMapInterleave, CUtensorMapSwizzle, CUtensorMapL2promotion, CUtensorMapFloatOOBfill);
static void map_2d(PFN_encodeTiled enc, CUtensorMap* m, const void* ptr, uint64_t rows, uint64_t cols, uint32_t brows, uint32_t bcols, CUtensorMapSwizzle sw) {
  cuuint64_t dims[2] = {cols, rows}; cuuint64_t strides[1] = {cols * 2}; cuuint32_t box[2] = {bcols, brows}; cuuint32_t es[2] = {1, 1};
  enc(m, CU_TENSOR_MAP_DATA_TYPE_BFLOAT16, 2, (void*)ptr, dims, strides, box, es, CU_TENSOR_MAP_INTERLEAVE_NONE, sw,
      CU_TENSOR_MAP_L2_PROMOTION_L2_256B, CU_TENSOR_MAP_FLOAT_OOB_FILL_NONE);
}
static void map_w(PFN_encodeTiled enc, CUtensorMap* m, const void* ptr, uint64_t rows, uint64_t ld, uint64_t col0, uint32_t nchunks, uint32_t parts) {
  cuuint64_t dims[4] = {64, rows, 8 * nchunks, parts}; cuuint64_t strides[3] = {ld * 2, 128, 8 * nchunks * 128};
  cuuint32_t box[4] = {64, 64, nchunks, parts}; cuuint32_t es[4] = {1, 1, 1, 1};
  enc(m, CU_TENSOR_MAP_DATA_TYPE_BFLOAT16, 4, (void*)((const bf16*)ptr + col0), dims, strides, box, es, CU_TENSOR_MAP_INTERLEAVE_NONE,
      CU_TENSOR_MAP_SWIZZLE_128B, CU_TENSOR_MAP_L2_PROMOTION_L2_256B, CU_TENSOR_MAP_FLOAT_OOB_FILL_NONE);
}

extern "C" void kernel_launch(void* const* d_in, const int* in_sizes, int n_in, void* d_out, int out_size) {
  void* fp = nullptr; cudaDriverEntryPointQueryResult qr;
  cudaGetDriverEntryPoint("cuTensorMapEncodeTiled", &fp, cudaEnableDefault, &qr);
  PFN_encodeTiled enc = (PFN_encodeTiled)fp;
  Params p;
  map_2d(enc, &p.tm_x, d_in[0], SEQ, DM, 64, 64, CU_TENSOR_MAP_SWIZZLE_128B);
  map_2d(enc, &p.tm_out, d_out, SEQ, DM, 16, 64, CU_TENSOR_MAP_SWIZZLE_128B);
  map_w(enc, &p.tm_b[0], d_in[1], DM, 3 * DM, DM, 2, 2);
  map_w(enc, &p.tm_b[1], d_in[1], DM, 3 * DM, 0, 2, 1);
  map_w(enc, &p.tm_b[2], d_in[3], DM, DM, 0, 2, 1);
  map_w(enc, &p.tm_b[3], d_in[5], DM, FF, 0, 3, 1);
  map_w(enc, &p.tm_b[4], d_in[5], DM, FF, 1536, 2, 1);
  map_w(enc, &p.tm_b[5], d_in[5], DM, FF, 2560, 2, 1);
  map_w(enc, &p.tm_b[6], d_in[7], FF, DM, 0, 2, 1);
  map_2d(enc, &p.tm_wphi, d_in[2], 1024, 32, 128, 32, CU_TENSOR_MAP_SWIZZLE_64B);
  p.x = (const bf16*)d_in[0]; p.wqkv = (const bf16*)d_in[1]; p.wo = (const bf16*)d_in[3]; p.w1 = (const bf16*)d_in[5]; p.w2 = (const bf16*)d_in[7];
  p.b1 = (const bf16*)d_in[6]; p.b2 = (const bf16*)d_in[8]; p.c = (const bf16*)d_in[9]; p.wmod = (const bf16*)d_in[10];
  cudaFuncSetAttribute(mega_kernel, cudaFuncAttributeMaxDynamicSharedMemorySize, SM_TOTAL);
  mega_kernel<<<128, 384, SM_TOTAL>>>(p);
}
```

```cpp
#include <cuda_runtime.h>
#include <cuda_bf16.h>
#include <cuda.h>
#include <stdint.h>
#include <type_traits>

typedef __nv_bfloat16 bf16;
#define SPIN_LIMIT (1u << 21)
constexpr int SEQ = 2048, DM = 1024, FF = 3584;

__device__ uint32_t g_epoch;
__device__ uint32_t g_done;
__device__ uint2 g_modpk[3072 + 7 * 1024];
__device__ uint4 g_st1pk[SEQ];
__device__ uint4 g_st2pk[8 * SEQ];
__device__ uint4 g_utpk[FF];
__device__ __align__(1024) uint8_t g_act[16 * 104 * 16384];
__device__ uint4 g_x1f[128 * 8 * 256];
__device__ float4 g_kvacc[2][32 * 5 * 128];
__device__ __align__(128) uint32_t g_flag[(16 * 10 + 8) * 32];
#define g_kvflag (g_flag + 16 * 10 * 32)
#define TL(i) do { } while (0)

__device__ __forceinline__ uint32_t smem_u32(const void* p) { return (uint32_t)__cvta_generic_to_shared(p); }
__device__ __forceinline__ void mbar_init(uint32_t bar, uint32_t cnt) { asm volatile("mbarrier.init.shared::cta.b64 [%0], %1;" :: "r"(bar), "r"(cnt) : "memory"); }
__device__ __forceinline__ void mbar_expect_tx(uint32_t bar, uint32_t bytes) { asm volatile("mbarrier.arrive.expect_tx.shared::cta.b64 _, [%0], %1;" :: "r"(bar), "r"(bytes) : "memory"); }
__device__ __forceinline__ void mbar_arrive(uint32_t bar) { asm volatile("mbarrier.arrive.shared::cta.b64 _, [%0];" :: "r"(bar) : "memory"); }
__device__ __forceinline__ void mbar_arrive_cluster(uint32_t bar, uint32_t cta) {
  asm volatile("{\n.reg .b32 ra;\nmapa.shared::cluster.u32 ra, %0, %1;\nmbarrier.arrive.shared::cluster.b64 _, [ra];\n}\n" :: "r"(bar), "r"(cta) : "memory");
}
__device__ __forceinline__ bool mbar_try_wait(uint32_t bar, uint32_t parity) {
  uint32_t ok;
  asm volatile("{\n.reg .pred p;\nmbarrier.try_wait.parity.shared::cta.b64 p, [%1], %2;\nselp.u32 %0, 1, 0, p;\n}\n" : "=r"(ok) : "r"(bar), "r"(parity) : "memory");
  return ok;
}
__device__ __forceinline__ void spin_guard(uint32_t n) {
  asm volatile("{\n.reg .pred p;\n.reg .b32 a;\nmov.b32 a, 0x00fffffd;\nsetp.gt.u32 p, %0, %1;\n@p st.shared.u32 [a], %0;\n}\n" :: "r"(n), "n"(SPIN_LIMIT) : "memory");
}
#define MBAR_WAIT(bar, par, lim) "mov.b32 n, 0;\nmov.b32 a, 0x00fffffd;\nWAIT_LOOP:\nmbarrier.try_wait.parity.shared::cta.b64 p, [" bar "], " par ";\n@p bra WAIT_DONE;\n" \
  "add.u32 n, n, 1;\nsetp.gt.u32 p, n, " lim ";\n@p st.shared.u32 [a], n;\nbra WAIT_LOOP;\nWAIT_DONE:\n"
__device__ __forceinline__ void mbar_wait(uint32_t bar, uint32_t parity) {
  asm volatile("{\n.reg .pred p;\n.reg .b32 n, a;\n" MBAR_WAIT("%0", "%1", "%2") "}\n" :: "r"(bar), "r"(parity), "n"(SPIN_LIMIT) : "memory");
}
__device__ __forceinline__ void tma_load_2d(uint32_t dst, const CUtensorMap* tm, uint32_t bar, int c0, int c1) {
  asm volatile("cp.async.bulk.tensor.2d.shared::cluster.global.mbarrier::complete_tx::bytes [%0], [%1, {%3, %4}], [%2];"
    :: "r"(dst), "l"(tm), "r"(bar), "r"(c0), "r"(c1) : "memory");
}
__device__ __forceinline__ void tma_load_2d_mc(uint32_t dst, const CUtensorMap* tm, uint32_t bar, int c0, int c1, uint16_t mask) {
  asm volatile("cp.async.bulk.tensor.2d.shared::cluster.global.mbarrier::complete_tx::bytes.multicast::cluster [%0], [%1, {%3, %4}], [%2], %5;"
    :: "r"(dst), "l"(tm), "r"(bar), "r"(c0), "r"(c1), "h"(mask) : "memory");
}
__device__ __forceinline__ void tma_load_4d(uint32_t dst, const CUtensorMap* tm, uint32_t bar, int c1, int c2) {
  asm volatile("cp.async.bulk.tensor.4d.shared::cluster.global.mbarrier::complete_tx::bytes [%0], [%1, {%5, %3, %4, %5}], [%2];"
    :: "r"(dst), "l"(tm), "r"(bar), "r"(c1), "r"(c2), "r"(0) : "memory");
}
__device__ __forceinline__ void tma_load_3d(uint32_t dst, const CUtensorMap* tm, uint32_t bar, int c0, int c1) {
  asm volatile("cp.async.bulk.tensor.3d.shared::cluster.global.mbarrier::complete_tx::bytes [%0], [%1, {%3, %4, %5}], [%2];"
    :: "r"(dst), "l"(tm), "r"(bar), "r"(c0), "r"(c1), "r"(0) : "memory");
}
__device__ __forceinline__ void tma_store_2d(const CUtensorMap* tm, uint32_t src, int c0, int c1) {
  asm volatile("cp.async.bulk.tensor.2d.global.shared::cta.bulk_group [%0, {%2, %3}], [%1];" :: "l"(tm), "r"(src), "r"(c0), "r"(c1) : "memory");
}
__device__ __forceinline__ void bulk_commit() { asm volatile("cp.async.bulk.commit_group;" ::: "memory"); }
__device__ __forceinline__ void bulk_wait_read0() { asm volatile("cp.async.bulk.wait_group.read 0;" ::: "memory"); }
__device__ __forceinline__ void bulk_wait0() { asm volatile("cp.async.bulk.wait_group 0;" ::: "memory"); }
__device__ __forceinline__ void fence_async() { asm volatile("fence.proxy.async;" ::: "memory"); }
__device__ __forceinline__ void fence_async_smem() { asm volatile("fence.proxy.async.shared::cta;" ::: "memory"); }
__device__ __forceinline__ void prefetch_tmap(const CUtensorMap* tm) { asm volatile("prefetch.tensormap [%0];" :: "l"(tm) : "memory"); }
__device__ __forceinline__ void wgmma_fence() { asm volatile("wgmma.fence.sync.aligned;" ::: "memory"); }
__device__ __forceinline__ void wgmma_commit() { asm volatile("wgmma.commit_group.sync.aligned;" ::: "memory"); }
template<int N> __device__ __forceinline__ void wgmma_wait() { asm volatile("wgmma.wait_group.sync.aligned %0;" :: "n"(N) : "memory"); }
__device__ __forceinline__ uint32_t desc_lo(uint32_t addr, uint32_t lbo) { return ((addr & 0x3FFFF) >> 4) | ((lbo >> 4) << 16); }
constexpr uint32_t H128 = 0x40000040u, H64 = 0x80000020u;
__device__ __forceinline__ void cluster_sync() {
  asm volatile("barrier.cluster.arrive.release.aligned;\nbarrier.cluster.wait.acquire.aligned;" ::: "memory");
}
__device__ __forceinline__ uint64_t gtimer() { uint64_t t; asm volatile("mov.u64 %0, %%globaltimer;" : "=l"(t)); return t; }
template<int R> __device__ __forceinline__ void reg_alloc() { asm volatile("setmaxnreg.inc.sync.aligned.u32 %0;" :: "n"(R)); }
template<int R> __device__ __forceinline__ void reg_dealloc() { asm volatile("setmaxnreg.dec.sync.aligned.u32 %0;" :: "n"(R)); }
__device__ __forceinline__ void bar_sync(int id, int n) { asm volatile("bar.sync %0, %1;" :: "r"(id), "r"(n) : "memory"); }
__device__ __forceinline__ uint32_t pack_bf16(float lo, float hi) { uint32_t r; asm("cvt.rn.bf16x2.f32 %0, %1, %2;" : "=r"(r) : "f"(hi), "f"(lo)); return r; }
__device__ __forceinline__ float bf_lo(uint32_t v) { return __uint_as_float(v << 16); }
__device__ __forceinline__ float bf_hi(uint32_t v) { return __uint_as_float(v & 0xffff0000u); }
__device__ __forceinline__ float bf_round(float v) { return bf_lo(pack_bf16(v, 0.f)); }
__device__ __forceinline__ void stmatrix_x4(uint32_t addr, uint32_t r0, uint32_t r1, uint32_t r2, uint32_t r3) {
  asm volatile("stmatrix.sync.aligned.m8n8.x4.shared.b16 [%0], {%1, %2, %3, %4};" :: "r"(addr), "r"(r0), "r"(r1), "r"(r2), "r"(r3) : "memory");
}
__device__ __forceinline__ void ldmatrix_x4(uint32_t addr, uint32_t& r0, uint32_t& r1, uint32_t& r2, uint32_t& r3) {
  asm volatile("ldmatrix.sync.aligned.m8n8.x4.shared.b16 {%0, %1, %2, %3}, [%4];" : "=r"(r0), "=r"(r1), "=r"(r2), "=r"(r3) : "r"(addr) : "memory");
}
__device__ __forceinline__ void ldmatrix_x4t(uint32_t addr, uint32_t& r0, uint32_t& r1, uint32_t& r2, uint32_t& r3) {
  asm volatile("ldmatrix.sync.aligned.m8n8.x4.trans.shared.b16 {%0, %1, %2, %3}, [%4];" : "=r"(r0), "=r"(r1), "=r"(r2), "=r"(r3) : "r"(addr) : "memory");
}
__device__ __forceinline__ uint32_t ld_acquire(const uint32_t* p) { uint32_t v; asm volatile("ld.acquire.gpu.global.u32 %0, [%1];" : "=r"(v) : "l"(p) : "memory"); return v; }
__device__ __forceinline__ uint32_t ld_relaxed(const uint32_t* p) { uint32_t v; asm volatile("ld.relaxed.gpu.global.u32 %0, [%1];" : "=r"(v) : "l"(p) : "memory"); return v; }
__device__ __forceinline__ void st_release(uint32_t* p, uint32_t v) { asm volatile("st.release.gpu.global.u32 [%0], %1;" :: "l"(p), "r"(v) : "memory"); }
__device__ __forceinline__ uint4 ld_vol4(const void* p) { uint4 v; asm volatile("ld.volatile.global.v4.u32 {%0, %1, %2, %3}, [%4];" : "=r"(v.x), "=r"(v.y), "=r"(v.z), "=r"(v.w) : "l"(p) : "memory"); return v; }
__device__ __forceinline__ uint2 ld_vol2(const void* p) { uint2 v; asm volatile("ld.volatile.global.v2.u32 {%0, %1}, [%2];" : "=r"(v.x), "=r"(v.y) : "l"(p) : "memory"); return v; }
__device__ __forceinline__ void st_vol2(void* p, uint32_t a, uint32_t b) { asm volatile("st.volatile.global.v2.u32 [%0], {%1, %2};" :: "l"(p), "r"(a), "r"(b) : "memory"); }
__device__ __forceinline__ void st_vol4(void* p, uint32_t a, uint32_t b, uint32_t c, uint32_t d) { asm volatile("st.volatile.global.v4.u32 [%0], {%1, %2, %3, %4};" :: "l"(p), "r"(a), "r"(b), "r"(c), "r"(d) : "memory"); }
__device__ __forceinline__ uint4 ld_nc4(const void* p) { uint4 v; asm volatile("ld.global.nc.L1::no_allocate.v4.u32 {%0, %1, %2, %3}, [%4];" : "=r"(v.x), "=r"(v.y), "=r"(v.z), "=r"(v.w) : "l"(p)); return v; }
__device__ __forceinline__ uint32_t ld_nc1(const void* p) { uint32_t v; asm volatile("ld.global.nc.u32 %0, [%1];" : "=r"(v) : "l"(p)); return v; }
__device__ __forceinline__ void red_add4(float4* p, float a, float b, float c, float d) {
  asm volatile("red.global.add.v4.f32 [%0], {%1, %2, %3, %4};" :: "l"(p), "f"(a), "f"(b), "f"(c), "f"(d) : "memory");
}
__device__ __forceinline__ void sts4(uint32_t a, uint32_t x, uint32_t y, uint32_t z, uint32_t w) { asm volatile("st.shared.v4.u32 [%0], {%1, %2, %3, %4};" :: "r"(a), "r"(x), "r"(y), "r"(z), "r"(w) : "memory"); }
__device__ __forceinline__ void sts2(uint32_t a, uint32_t x, uint32_t y) { asm volatile("st.shared.v2.u32 [%0], {%1, %2};" :: "r"(a), "r"(x), "r"(y) : "memory"); }
__device__ __forceinline__ void sts1(uint32_t a, uint32_t x) { asm volatile("st.shared.u32 [%0], %1;" :: "r"(a), "r"(x) : "memory"); }
__device__ __forceinline__ uint4 lds4(uint32_t a) { uint4 v; asm volatile("ld.shared.v4.u32 {%0, %1, %2, %3}, [%4];" : "=r"(v.x), "=r"(v.y), "=r"(v.z), "=r"(v.w) : "r"(a) : "memory"); return v; }
__device__ __forceinline__ uint2 lds2(uint32_t a) { uint2 v; asm volatile("ld.shared.v2.u32 {%0, %1}, [%2];" : "=r"(v.x), "=r"(v.y) : "r"(a) : "memory"); return v; }
__device__ __forceinline__ uint32_t lds1(uint32_t a) { uint32_t v; asm volatile("ld.shared.u32 %0, [%1];" : "=r"(v) : "r"(a) : "memory"); return v; }
__device__ __forceinline__ float ex2(float x) { float y; asm("ex2.approx.ftz.f32 %0, %1;" : "=f"(y) : "f"(x)); return y; }
__device__ __forceinline__ float rcp(float x) { float y; asm("rcp.approx.ftz.f32 %0, %1;" : "=f"(y) : "f"(x)); return y; }
__device__ __forceinline__ void prefetch_l2(const void* p) { asm volatile("prefetch.global.L2 [%0];" :: "l"(p)); }

__device__ __forceinline__ void st_relaxed(uint32_t* p, uint32_t v) { asm volatile("st.relaxed.gpu.global.u32 [%0], %1;" :: "l"(p), "r"(v) : "memory"); }
__device__ __forceinline__ uint4 ld_nc4p(const void* p) { uint4 v; asm volatile("ld.global.nc.L1::no_allocate.L2::128B.v4.u32 {%0, %1, %2, %3}, [%4];" : "=r"(v.x), "=r"(v.y), "=r"(v.z), "=r"(v.w) : "l"(p)); return v; }
__device__ __forceinline__ uint32_t mapa(uint32_t a, uint32_t cta) { uint32_t r; asm("mapa.shared::cluster.u32 %0, %1, %2;" : "=r"(r) : "r"(a), "r"(cta)); return r; }
__device__ __forceinline__ void mbar_arrive_cl(uint32_t a) { asm volatile("mbarrier.arrive.shared::cluster.b64 _, [%0];" :: "r"(a) : "memory"); }
__device__ __forceinline__ void bulk_load_mc(uint32_t dst, const void* src, uint32_t bytes, uint32_t bar) {
  asm volatile("cp.async.bulk.shared::cluster.global.mbarrier::complete_tx::bytes.multicast::cluster [%0], [%1], %2, [%3], %4;"
    :: "r"(dst), "l"(src), "r"(bytes), "r"(bar), "h"((uint16_t)3) : "memory");
}
__device__ __forceinline__ void bulk_load(uint32_t dst, const void* src, uint32_t bytes, uint32_t bar) {
  asm volatile("cp.async.bulk.shared::cluster.global.mbarrier::complete_tx::bytes [%0], [%1], %2, [%3];" :: "r"(dst), "l"(src), "r"(bytes), "r"(bar) : "memory");
}
__device__ __forceinline__ void bar_arrive(int id, int n) { asm volatile("bar.arrive %0, %1;" :: "r"(id), "r"(n) : "memory"); }
__device__ __forceinline__ void bulk_store(void* dst, uint32_t src, uint32_t bytes) {
  asm volatile("cp.async.bulk.global.shared::cta.bulk_group [%0], [%1], %2;" :: "l"(dst), "r"(src), "r"(bytes) : "memory");
}
__device__ __forceinline__ void bulk_copy_peer(uint32_t dst, uint32_t src, uint32_t bytes, uint32_t bar) {
  asm volatile("cp.async.bulk.shared::cluster.shared::cta.mbarrier::complete_tx::bytes [%0], [%1], %2, [%3];" :: "r"(dst), "r"(src), "r"(bytes), "r"(bar) : "memory");
}
__device__ __forceinline__ void bulk_prefetch(const void* src, uint32_t bytes) { asm volatile("cp.async.bulk.prefetch.L2.global [%0], %1;" :: "l"(src), "r"(bytes) : "memory"); }
__device__ __forceinline__ void bulk_wait1() { asm volatile("cp.async.bulk.wait_group 1;" ::: "memory"); }
__device__ __forceinline__ void cluster_arrive() { asm volatile("barrier.cluster.arrive.relaxed.aligned;" ::: "memory"); }
__device__ __forceinline__ void cluster_wait() { asm volatile("barrier.cluster.wait.aligned;" ::: "memory"); }
__device__ __forceinline__ uint32_t hfma2(uint32_t a, uint32_t b, uint32_t c) { uint32_t r; asm("fma.rn.bf16x2 %0, %1, %2, %3;" : "=r"(r) : "r"(a), "r"(b), "r"(c)); return r; }
__device__ __forceinline__ uint32_t hmul2(uint32_t a, uint32_t b) { uint32_t r; asm("mul.rn.bf16x2 %0, %1, %2;" : "=r"(r) : "r"(a), "r"(b)); return r; }
__device__ __forceinline__ uint32_t pack_relu(float lo, float hi) { uint32_t r; asm("cvt.rn.relu.bf16x2.f32 %0, %1, %2;" : "=r"(r) : "f"(hi), "f"(lo)); return r; }
__device__ __forceinline__ uint2 ld_nc2(const void* p) { uint2 v; asm volatile("ld.global.nc.L1::no_allocate.v2.u32 {%0, %1}, [%2];" : "=r"(v.x), "=r"(v.y) : "l"(p)); return v; }
__device__ __forceinline__ void hmma(float (&d)[4], uint32_t a0, uint32_t a1, uint32_t a2, uint32_t a3, uint32_t b0, uint32_t b1) {
  asm("mma.sync.aligned.m16n8k16.row.col.f32.bf16.bf16.f32 {%0, %1, %2, %3}, {%4, %5, %6, %7}, {%8, %9}, {%0, %1, %2, %3};"
    : "+f"(d[0]), "+f"(d[1]), "+f"(d[2]), "+f"(d[3]) : "r"(a0), "r"(a1), "r"(a2), "r"(a3), "r"(b0), "r"(b1));
}
template<int N> __device__ __forceinline__ void fence_regs(float (&r)[N]) {
#pragma unroll
  for (int i = 0; i < N; i++) asm volatile("" : "+f"(r[i]) :: "memory");
}

template<int N> __device__ __forceinline__ void zero_regs(float (&r)[N]) {
#pragma unroll
  for (int i = 0; i < N; i++) asm volatile("mov.f32 %0, 0f00000000;" : "=f"(r[i]));
}

template<int TA, int TB, uint32_t HI> __device__ __forceinline__ void wgmma_ss_n192(float (&d)[96], uint32_t da, uint32_t db) {
  asm volatile("{\n.reg .pred p;\n.reg .b64 da, db;\nsetp.ne.b32 p, 1, 0;\nmov.b64 da, {%96, %100};\nmov.b64 db, {%97, %100};\n"
    "wgmma.mma_async.sync.aligned.m64n192k16.f32.bf16.bf16 {%0, %1, %2, %3, %4, %5, %6, %7, %8, %9, %10, %11, %12, %13, %14, %15, %16, %17, %18, %19, %20, %21, %22, %23, %24, %25, %26, %27, %28, %29, %30, %31, %32, %33, %34, %35, %36, %37, %38, %39, %40, %41, %42, %43, %44, %45, %46, %47, %48, %49, %50, %51, %52, %53, %54, %55, %56, %57, %58, %59, %60, %61, %62, %63, %64, %65, %66, %67, %68, %69, %70, %71, %72, %73, %74, %75, %76, %77, %78, %79, %80, %81, %82, %83, %84, %85, %86, %87, %88, %89, %90, %91, %92, %93, %94, %95}, da, db, p, 1, 1, %98, %99;\n}\n"
    : "+f"(d[0]), "+f"(d[1]), "+f"(d[2]), "+f"(d[3]), "+f"(d[4]), "+f"(d[5]), "+f"(d[6]), "+f"(d[7]), "+f"(d[8]), "+f"(d[9]), "+f"(d[10]), "+f"(d[11]), "+f"(d[12]), "+f"(d[13]), "+f"(d[14]), "+f"(d[15]), "+f"(d[16]), "+f"(d[17]), "+f"(d[18]), "+f"(d[19]), "+f"(d[20]), "+f"(d[21]), "+f"(d[22]), "+f"(d[23]), "+f"(d[24]), "+f"(d[25]), "+f"(d[26]), "+f"(d[27]), "+f"(d[28]), "+f"(d[29]), "+f"(d[30]), "+f"(d[31]), "+f"(d[32]), "+f"(d[33]), "+f"(d[34]), "+f"(d[35]), "+f"(d[36]), "+f"(d[37]), "+f"(d[38]), "+f"(d[39]), "+f"(d[40]), "+f"(d[41]), "+f"(d[42]), "+f"(d[43]), "+f"(d[44]), "+f"(d[45]), "+f"(d[46]), "+f"(d[47]), "+f"(d[48]), "+f"(d[49]), "+f"(d[50]), "+f"(d[51]), "+f"(d[52]), "+f"(d[53]), "+f"(d[54]), "+f"(d[55]), "+f"(d[56]), "+f"(d[57]), "+f"(d[58]), "+f"(d[59]), "+f"(d[60]), "+f"(d[61]), "+f"(d[62]), "+f"(d[63]), "+f"(d[64]), "+f"(d[65]), "+f"(d[66]), "+f"(d[67]), "+f"(d[68]), "+f"(d[69]), "+f"(d[70]), "+f"(d[71]), "+f"(d[72]), "+f"(d[73]), "+f"(d[74]), "+f"(d[75]), "+f"(d[76]), "+f"(d[77]), "+f"(d[78]), "+f"(d[79]), "+f"(d[80]), "+f"(d[81]), "+f"(d[82]), "+f"(d[83]), "+f"(d[84]), "+f"(d[85]), "+f"(d[86]), "+f"(d[87]), "+f"(d[88]), "+f"(d[89]), "+f"(d[90]), "+f"(d[91]), "+f"(d[92]), "+f"(d[93]), "+f"(d[94]), "+f"(d[95])
    : "r"(da), "r"(db), "n"(TA), "n"(TB), "n"(HI));
}
template<int TA, int TB, uint32_t HI> __device__ __forceinline__ void wgmma_ssz_n192(float (&d)[96], uint32_t da, uint32_t db) {
  asm volatile("{\n.reg .pred p;\n.reg .b64 da, db;\nsetp.ne.b32 p, 0, 0;\nmov.b64 da, {%96, %100};\nmov.b64 db, {%97, %100};\n"
    "wgmma.mma_async.sync.aligned.m64n192k16.f32.bf16.bf16 {%0, %1, %2, %3, %4, %5, %6, %7, %8, %9, %10, %11, %12, %13, %14, %15, %16, %17, %18, %19, %20, %21, %22, %23, %24, %25, %26, %27, %28, %29, %30, %31, %32, %33, %34, %35, %36, %37, %38, %39, %40, %41, %42, %43, %44, %45, %46, %47, %48, %49, %50, %51, %52, %53, %54, %55, %56, %57, %58, %59, %60, %61, %62, %63, %64, %65, %66, %67, %68, %69, %70, %71, %72, %73, %74, %75, %76, %77, %78, %79, %80, %81, %82, %83, %84, %85, %86, %87, %88, %89, %90, %91, %92, %93, %94, %95}, da, db, p, 1, 1, %98, %99;\n}\n"
    : "=f"(d[0]), "=f"(d[1]), "=f"(d[2]), "=f"(d[3]), "=f"(d[4]), "=f"(d[5]), "=f"(d[6]), "=f"(d[7]), "=f"(d[8]), "=f"(d[9]), "=f"(d[10]), "=f"(d[11]), "=f"(d[12]), "=f"(d[13]), "=f"(d[14]), "=f"(d[15]), "=f"(d[16]), "=f"(d[17]), "=f"(d[18]), "=f"(d[19]), "=f"(d[20]), "=f"(d[21]), "=f"(d[22]), "=f"(d[23]), "=f"(d[24]), "=f"(d[25]), "=f"(d[26]), "=f"(d[27]), "=f"(d[28]), "=f"(d[29]), "=f"(d[30]), "=f"(d[31]), "=f"(d[32]), "=f"(d[33]), "=f"(d[34]), "=f"(d[35]), "=f"(d[36]), "=f"(d[37]), "=f"(d[38]), "=f"(d[39]), "=f"(d[40]), "=f"(d[41]), "=f"(d[42]), "=f"(d[43]), "=f"(d[44]), "=f"(d[45]), "=f"(d[46]), "=f"(d[47]), "=f"(d[48]), "=f"(d[49]), "=f"(d[50]), "=f"(d[51]), "=f"(d[52]), "=f"(d[53]), "=f"(d[54]), "=f"(d[55]), "=f"(d[56]), "=f"(d[57]), "=f"(d[58]), "=f"(d[59]), "=f"(d[60]), "=f"(d[61]), "=f"(d[62]), "=f"(d[63]), "=f"(d[64]), "=f"(d[65]), "=f"(d[66]), "=f"(d[67]), "=f"(d[68]), "=f"(d[69]), "=f"(d[70]), "=f"(d[71]), "=f"(d[72]), "=f"(d[73]), "=f"(d[74]), "=f"(d[75]), "=f"(d[76]), "=f"(d[77]), "=f"(d[78]), "=f"(d[79]), "=f"(d[80]), "=f"(d[81]), "=f"(d[82]), "=f"(d[83]), "=f"(d[84]), "=f"(d[85]), "=f"(d[86]), "=f"(d[87]), "=f"(d[88]), "=f"(d[89]), "=f"(d[90]), "=f"(d[91]), "=f"(d[92]), "=f"(d[93]), "=f"(d[94]), "=f"(d[95])
    : "r"(da), "r"(db), "n"(TA), "n"(TB), "n"(HI));
}
template<int TA, int TB, uint32_t HI> __device__ __forceinline__ void wgmma_ss_n128(float (&d)[64], uint32_t da, uint32_t db) {
  asm volatile("{\n.reg .pred p;\n.reg .b64 da, db;\nsetp.ne.b32 p, 1, 0;\nmov.b64 da, {%64, %68};\nmov.b64 db, {%65, %68};\n"
    "wgmma.mma_async.sync.aligned.m64n128k16.f32.bf16.bf16 {%0, %1, %2, %3, %4, %5, %6, %7, %8, %9, %10, %11, %12, %13, %14, %15, %16, %17, %18, %19, %20, %21, %22, %23, %24, %25, %26, %27, %28, %29, %30, %31, %32, %33, %34, %35, %36, %37, %38, %39, %40, %41, %42, %43, %44, %45, %46, %47, %48, %49, %50, %51, %52, %53, %54, %55, %56, %57, %58, %59, %60, %61, %62, %63}, da, db, p, 1, 1, %66, %67;\n}\n"
    : "+f"(d[0]), "+f"(d[1]), "+f"(d[2]), "+f"(d[3]), "+f"(d[4]), "+f"(d[5]), "+f"(d[6]), "+f"(d[7]), "+f"(d[8]), "+f"(d[9]), "+f"(d[10]), "+f"(d[11]), "+f"(d[12]), "+f"(d[13]), "+f"(d[14]), "+f"(d[15]), "+f"(d[16]), "+f"(d[17]), "+f"(d[18]), "+f"(d[19]), "+f"(d[20]), "+f"(d[21]), "+f"(d[22]), "+f"(d[23]), "+f"(d[24]), "+f"(d[25]), "+f"(d[26]), "+f"(d[27]), "+f"(d[28]), "+f"(d[29]), "+f"(d[30]), "+f"(d[31]), "+f"(d[32]), "+f"(d[33]), "+f"(d[34]), "+f"(d[35]), "+f"(d[36]), "+f"(d[37]), "+f"(d[38]), "+f"(d[39]), "+f"(d[40]), "+f"(d[41]), "+f"(d[42]), "+f"(d[43]), "+f"(d[44]), "+f"(d[45]), "+f"(d[46]), "+f"(d[47]), "+f"(d[48]), "+f"(d[49]), "+f"(d[50]), "+f"(d[51]), "+f"(d[52]), "+f"(d[53]), "+f"(d[54]), "+f"(d[55]), "+f"(d[56]), "+f"(d[57]), "+f"(d[58]), "+f"(d[59]), "+f"(d[60]), "+f"(d[61]), "+f"(d[62]), "+f"(d[63])
    : "r"(da), "r"(db), "n"(TA), "n"(TB), "n"(HI));
}
template<int TA, int TB, uint32_t HI> __device__ __forceinline__ void wgmma_ssz_n128(float (&d)[64], uint32_t da, uint32_t db) {
  asm volatile("{\n.reg .pred p;\n.reg .b64 da, db;\nsetp.ne.b32 p, 0, 0;\nmov.b64 da, {%64, %68};\nmov.b64 db, {%65, %68};\n"
    "wgmma.mma_async.sync.aligned.m64n128k16.f32.bf16.bf16 {%0, %1, %2, %3, %4, %5, %6, %7, %8, %9, %10, %11, %12, %13, %14, %15, %16, %17, %18, %19, %20, %21, %22, %23, %24, %25, %26, %27, %28, %29, %30, %31, %32, %33, %34, %35, %36, %37, %38, %39, %40, %41, %42, %43, %44, %45, %46, %47, %48, %49, %50, %51, %52, %53, %54, %55, %56, %57, %58, %59, %60, %61, %62, %63}, da, db, p, 1, 1, %66, %67;\n}\n"
    : "=f"(d[0]), "=f"(d[1]), "=f"(d[2]), "=f"(d[3]), "=f"(d[4]), "=f"(d[5]), "=f"(d[6]), "=f"(d[7]), "=f"(d[8]), "=f"(d[9]), "=f"(d[10]), "=f"(d[11]), "=f"(d[12]), "=f"(d[13]), "=f"(d[14]), "=f"(d[15]), "=f"(d[16]), "=f"(d[17]), "=f"(d[18]), "=f"(d[19]), "=f"(d[20]), "=f"(d[21]), "=f"(d[22]), "=f"(d[23]), "=f"(d[24]), "=f"(d[25]), "=f"(d[26]), "=f"(d[27]), "=f"(d[28]), "=f"(d[29]), "=f"(d[30]), "=f"(d[31]), "=f"(d[32]), "=f"(d[33]), "=f"(d[34]), "=f"(d[35]), "=f"(d[36]), "=f"(d[37]), "=f"(d[38]), "=f"(d[39]), "=f"(d[40]), "=f"(d[41]), "=f"(d[42]), "=f"(d[43]), "=f"(d[44]), "=f"(d[45]), "=f"(d[46]), "=f"(d[47]), "=f"(d[48]), "=f"(d[49]), "=f"(d[50]), "=f"(d[51]), "=f"(d[52]), "=f"(d[53]), "=f"(d[54]), "=f"(d[55]), "=f"(d[56]), "=f"(d[57]), "=f"(d[58]), "=f"(d[59]), "=f"(d[60]), "=f"(d[61]), "=f"(d[62]), "=f"(d[63])
    : "r"(da), "r"(db), "n"(TA), "n"(TB), "n"(HI));
}
template<int TA, int TB, uint32_t HI> __device__ __forceinline__ void wgmma_ssp_n128(float (&d)[64], uint32_t da, uint32_t db, uint32_t sd) {
  asm volatile("{\n.reg .pred p;\n.reg .b64 da, db;\nsetp.ne.b32 p, %69, 0;\nmov.b64 da, {%64, %68};\nmov.b64 db, {%65, %68};\n"
    "wgmma.mma_async.sync.aligned.m64n128k16.f32.bf16.bf16 {%0, %1, %2, %3, %4, %5, %6, %7, %8, %9, %10, %11, %12, %13, %14, %15, %16, %17, %18, %19, %20, %21, %22, %23, %24, %25, %26, %27, %28, %29, %30, %31, %32, %33, %34, %35, %36, %37, %38, %39, %40, %41, %42, %43, %44, %45, %46, %47, %48, %49, %50, %51, %52, %53, %54, %55, %56, %57, %58, %59, %60, %61, %62, %63}, da, db, p, 1, 1, %66, %67;\n}\n"
    : "+f"(d[0]), "+f"(d[1]), "+f"(d[2]), "+f"(d[3]), "+f"(d[4]), "+f"(d[5]), "+f"(d[6]), "+f"(d[7]), "+f"(d[8]), "+f"(d[9]), "+f"(d[10]), "+f"(d[11]), "+f"(d[12]), "+f"(d[13]), "+f"(d[14]), "+f"(d[15]), "+f"(d[16]), "+f"(d[17]), "+f"(d[18]), "+f"(d[19]), "+f"(d[20]), "+f"(d[21]), "+f"(d[22]), "+f"(d[23]), "+f"(d[24]), "+f"(d[25]), "+f"(d[26]), "+f"(d[27]), "+f"(d[28]), "+f"(d[29]), "+f"(d[30]), "+f"(d[31]), "+f"(d[32]), "+f"(d[33]), "+f"(d[34]), "+f"(d[35]), "+f"(d[36]), "+f"(d[37]), "+f"(d[38]), "+f"(d[39]), "+f"(d[40]), "+f"(d[41]), "+f"(d[42]), "+f"(d[43]), "+f"(d[44]), "+f"(d[45]), "+f"(d[46]), "+f"(d[47]), "+f"(d[48]), "+f"(d[49]), "+f"(d[50]), "+f"(d[51]), "+f"(d[52]), "+f"(d[53]), "+f"(d[54]), "+f"(d[55]), "+f"(d[56]), "+f"(d[57]), "+f"(d[58]), "+f"(d[59]), "+f"(d[60]), "+f"(d[61]), "+f"(d[62]), "+f"(d[63])
    : "r"(da), "r"(db), "n"(TA), "n"(TB), "n"(HI), "r"(sd));
}
template<int TA, int TB, uint32_t HI> __device__ __forceinline__ void wgmma_ss_n40(float (&d)[20], uint32_t da, uint32_t db) {
  asm volatile("{\n.reg .pred p;\n.reg .b64 da, db;\nsetp.ne.b32 p, 1, 0;\nmov.b64 da, {%20, %24};\nmov.b64 db, {%21, %24};\n"
    "wgmma.mma_async.sync.aligned.m64n40k16.f32.bf16.bf16 {%0, %1, %2, %3, %4, %5, %6, %7, %8, %9, %10, %11, %12, %13, %14, %15, %16, %17, %18, %19}, da, db, p, 1, 1, %22, %23;\n}\n"
    : "+f"(d[0]), "+f"(d[1]), "+f"(d[2]), "+f"(d[3]), "+f"(d[4]), "+f"(d[5]), "+f"(d[6]), "+f"(d[7]), "+f"(d[8]), "+f"(d[9]), "+f"(d[10]), "+f"(d[11]), "+f"(d[12]), "+f"(d[13]), "+f"(d[14]), "+f"(d[15]), "+f"(d[16]), "+f"(d[17]), "+f"(d[18]), "+f"(d[19])
    : "r"(da), "r"(db), "n"(TA), "n"(TB), "n"(HI));
}
template<int TA, int TB, uint32_t HI> __device__ __forceinline__ void wgmma_ssz_n40(float (&d)[20], uint32_t da, uint32_t db) {
  asm volatile("{\n.reg .pred p;\n.reg .b64 da, db;\nsetp.ne.b32 p, 0, 0;\nmov.b64 da, {%20, %24};\nmov.b64 db, {%21, %24};\n"
    "wgmma.mma_async.sync.aligned.m64n40k16.f32.bf16.bf16 {%0, %1, %2, %3, %4, %5, %6, %7, %8, %9, %10, %11, %12, %13, %14, %15, %16, %17, %18, %19}, da, db, p, 1, 1, %22, %23;\n}\n"
    : "=f"(d[0]), "=f"(d[1]), "=f"(d[2]), "=f"(d[3]), "=f"(d[4]), "=f"(d[5]), "=f"(d[6]), "=f"(d[7]), "=f"(d[8]), "=f"(d[9]), "=f"(d[10]), "=f"(d[11]), "=f"(d[12]), "=f"(d[13]), "=f"(d[14]), "=f"(d[15]), "=f"(d[16]), "=f"(d[17]), "=f"(d[18]), "=f"(d[19])
    : "r"(da), "r"(db), "n"(TA), "n"(TB), "n"(HI));
}
template<int TB, uint32_t HI> __device__ __forceinline__ void wgmma_rs_n256(float (&d)[128], uint32_t a0, uint32_t a1, uint32_t a2, uint32_t a3, uint32_t db) {
  asm volatile("{\n.reg .pred p;\n.reg .b64 db;\nsetp.ne.b32 p, 1, 0;\nmov.b64 db, {%132, %134};\n"
    "wgmma.mma_async.sync.aligned.m64n256k16.f32.bf16.bf16 {%0, %1, %2, %3, %4, %5, %6, %7, %8, %9, %10, %11, %12, %13, %14, %15, %16, %17, %18, %19, %20, %21, %22, %23, %24, %25, %26, %27, %28, %29, %30, %31, %32, %33, %34, %35, %36, %37, %38, %39, %40, %41, %42, %43, %44, %45, %46, %47, %48, %49, %50, %51, %52, %53, %54, %55, %56, %57, %58, %59, %60, %61, %62, %63, %64, %65, %66, %67, %68, %69, %70, %71, %72, %73, %74, %75, %76, %77, %78, %79, %80, %81, %82, %83, %84, %85, %86, %87, %88, %89, %90, %91, %92, %93, %94, %95, %96, %97, %98, %99, %100, %101, %102, %103, %104, %105, %106, %107, %108, %109, %110, %111, %112, %113, %114, %115, %116, %117, %118, %119, %120, %121, %122, %123, %124, %125, %126, %127}, {%128, %129, %130, %131}, db, p, 1, 1, %133;\n}\n"
    : "+f"(d[0]), "+f"(d[1]), "+f"(d[2]), "+f"(d[3]), "+f"(d[4]), "+f"(d[5]), "+f"(d[6]), "+f"(d[7]), "+f"(d[8]), "+f"(d[9]), "+f"(d[10]), "+f"(d[11]), "+f"(d[12]), "+f"(d[13]), "+f"(d[14]), "+f"(d[15]), "+f"(d[16]), "+f"(d[17]), "+f"(d[18]), "+f"(d[19]), "+f"(d[20]), "+f"(d[21]), "+f"(d[22]), "+f"(d[23]), "+f"(d[24]), "+f"(d[25]), "+f"(d[26]), "+f"(d[27]), "+f"(d[28]), "+f"(d[29]), "+f"(d[30]), "+f"(d[31]), "+f"(d[32]), "+f"(d[33]), "+f"(d[34]), "+f"(d[35]), "+f"(d[36]), "+f"(d[37]), "+f"(d[38]), "+f"(d[39]), "+f"(d[40]), "+f"(d[41]), "+f"(d[42]), "+f"(d[43]), "+f"(d[44]), "+f"(d[45]), "+f"(d[46]), "+f"(d[47]), "+f"(d[48]), "+f"(d[49]), "+f"(d[50]), "+f"(d[51]), "+f"(d[52]), "+f"(d[53]), "+f"(d[54]), "+f"(d[55]), "+f"(d[56]), "+f"(d[57]), "+f"(d[58]), "+f"(d[59]), "+f"(d[60]), "+f"(d[61]), "+f"(d[62]), "+f"(d[63]), "+f"(d[64]), "+f"(d[65]), "+f"(d[66]), "+f"(d[67]), "+f"(d[68]), "+f"(d[69]), "+f"(d[70]), "+f"(d[71]), "+f"(d[72]), "+f"(d[73]), "+f"(d[74]), "+f"(d[75]), "+f"(d[76]), "+f"(d[77]), "+f"(d[78]), "+f"(d[79]), "+f"(d[80]), "+f"(d[81]), "+f"(d[82]), "+f"(d[83]), "+f"(d[84]), "+f"(d[85]), "+f"(d[86]), "+f"(d[87]), "+f"(d[88]), "+f"(d[89]), "+f"(d[90]), "+f"(d[91]), "+f"(d[92]), "+f"(d[93]), "+f"(d[94]), "+f"(d[95]), "+f"(d[96]), "+f"(d[97]), "+f"(d[98]), "+f"(d[99]), "+f"(d[100]), "+f"(d[101]), "+f"(d[102]), "+f"(d[103]), "+f"(d[104]), "+f"(d[105]), "+f"(d[106]), "+f"(d[107]), "+f"(d[108]), "+f"(d[109]), "+f"(d[110]), "+f"(d[111]), "+f"(d[112]), "+f"(d[113]), "+f"(d[114]), "+f"(d[115]), "+f"(d[116]), "+f"(d[117]), "+f"(d[118]), "+f"(d[119]), "+f"(d[120]), "+f"(d[121]), "+f"(d[122]), "+f"(d[123]), "+f"(d[124]), "+f"(d[125]), "+f"(d[126]), "+f"(d[127])
    : "r"(a0), "r"(a1), "r"(a2), "r"(a3), "r"(db), "n"(TB), "n"(HI));
}
template<int TB, uint32_t HI> __device__ __forceinline__ void wgmma_rsz_n256(float (&d)[128], uint32_t a0, uint32_t a1, uint32_t a2, uint32_t a3, uint32_t db) {
  asm volatile("{\n.reg .pred p;\n.reg .b64 db;\nsetp.ne.b32 p, 0, 0;\nmov.b64 db, {%132, %134};\n"
    "wgmma.mma_async.sync.aligned.m64n256k16.f32.bf16.bf16 {%0, %1, %2, %3, %4, %5, %6, %7, %8, %9, %10, %11, %12, %13, %14, %15, %16, %17, %18, %19, %20, %21, %22, %23, %24, %25, %26, %27, %28, %29, %30, %31, %32, %33, %34, %35, %36, %37, %38, %39, %40, %41, %42, %43, %44, %45, %46, %47, %48, %49, %50, %51, %52, %53, %54, %55, %56, %57, %58, %59, %60, %61, %62, %63, %64, %65, %66, %67, %68, %69, %70, %71, %72, %73, %74, %75, %76, %77, %78, %79, %80, %81, %82, %83, %84, %85, %86, %87, %88, %89, %90, %91, %92, %93, %94, %95, %96, %97, %98, %99, %100, %101, %102, %103, %104, %105, %106, %107, %108, %109, %110, %111, %112, %113, %114, %115, %116, %117, %118, %119, %120, %121, %122, %123, %124, %125, %126, %127}, {%128, %129, %130, %131}, db, p, 1, 1, %133;\n}\n"
    : "=f"(d[0]), "=f"(d[1]), "=f"(d[2]), "=f"(d[3]), "=f"(d[4]), "=f"(d[5]), "=f"(d[6]), "=f"(d[7]), "=f"(d[8]), "=f"(d[9]), "=f"(d[10]), "=f"(d[11]), "=f"(d[12]), "=f"(d[13]), "=f"(d[14]), "=f"(d[15]), "=f"(d[16]), "=f"(d[17]), "=f"(d[18]), "=f"(d[19]), "=f"(d[20]), "=f"(d[21]), "=f"(d[22]), "=f"(d[23]), "=f"(d[24]), "=f"(d[25]), "=f"(d[26]), "=f"(d[27]), "=f"(d[28]), "=f"(d[29]), "=f"(d[30]), "=f"(d[31]), "=f"(d[32]), "=f"(d[33]), "=f"(d[34]), "=f"(d[35]), "=f"(d[36]), "=f"(d[37]), "=f"(d[38]), "=f"(d[39]), "=f"(d[40]), "=f"(d[41]), "=f"(d[42]), "=f"(d[43]), "=f"(d[44]), "=f"(d[45]), "=f"(d[46]), "=f"(d[47]), "=f"(d[48]), "=f"(d[49]), "=f"(d[50]), "=f"(d[51]), "=f"(d[52]), "=f"(d[53]), "=f"(d[54]), "=f"(d[55]), "=f"(d[56]), "=f"(d[57]), "=f"(d[58]), "=f"(d[59]), "=f"(d[60]), "=f"(d[61]), "=f"(d[62]), "=f"(d[63]), "=f"(d[64]), "=f"(d[65]), "=f"(d[66]), "=f"(d[67]), "=f"(d[68]), "=f"(d[69]), "=f"(d[70]), "=f"(d[71]), "=f"(d[72]), "=f"(d[73]), "=f"(d[74]), "=f"(d[75]), "=f"(d[76]), "=f"(d[77]), "=f"(d[78]), "=f"(d[79]), "=f"(d[80]), "=f"(d[81]), "=f"(d[82]), "=f"(d[83]), "=f"(d[84]), "=f"(d[85]), "=f"(d[86]), "=f"(d[87]), "=f"(d[88]), "=f"(d[89]), "=f"(d[90]), "=f"(d[91]), "=f"(d[92]), "=f"(d[93]), "=f"(d[94]), "=f"(d[95]), "=f"(d[96]), "=f"(d[97]), "=f"(d[98]), "=f"(d[99]), "=f"(d[100]), "=f"(d[101]), "=f"(d[102]), "=f"(d[103]), "=f"(d[104]), "=f"(d[105]), "=f"(d[106]), "=f"(d[107]), "=f"(d[108]), "=f"(d[109]), "=f"(d[110]), "=f"(d[111]), "=f"(d[112]), "=f"(d[113]), "=f"(d[114]), "=f"(d[115]), "=f"(d[116]), "=f"(d[117]), "=f"(d[118]), "=f"(d[119]), "=f"(d[120]), "=f"(d[121]), "=f"(d[122]), "=f"(d[123]), "=f"(d[124]), "=f"(d[125]), "=f"(d[126]), "=f"(d[127])
    : "r"(a0), "r"(a1), "r"(a2), "r"(a3), "r"(db), "n"(TB), "n"(HI));
}
template<int TB, uint32_t HI> __device__ __forceinline__ void wgmma_rs_n40(float (&d)[20], uint32_t a0, uint32_t a1, uint32_t a2, uint32_t a3, uint32_t db) {
  asm volatile("{\n.reg .pred p;\n.reg .b64 db;\nsetp.ne.b32 p, 1, 0;\nmov.b64 db, {%24, %26};\n"
    "wgmma.mma_async.sync.aligned.m64n40k16.f32.bf16.bf16 {%0, %1, %2, %3, %4, %5, %6, %7, %8, %9, %10, %11, %12, %13, %14, %15, %16, %17, %18, %19}, {%20, %21, %22, %23}, db, p, 1, 1, %25;\n}\n"
    : "+f"(d[0]), "+f"(d[1]), "+f"(d[2]), "+f"(d[3]), "+f"(d[4]), "+f"(d[5]), "+f"(d[6]), "+f"(d[7]), "+f"(d[8]), "+f"(d[9]), "+f"(d[10]), "+f"(d[11]), "+f"(d[12]), "+f"(d[13]), "+f"(d[14]), "+f"(d[15]), "+f"(d[16]), "+f"(d[17]), "+f"(d[18]), "+f"(d[19])
    : "r"(a0), "r"(a1), "r"(a2), "r"(a3), "r"(db), "n"(TB), "n"(HI));
}
template<int TB, uint32_t HI> __device__ __forceinline__ void wgmma_rsz_n40(float (&d)[20], uint32_t a0, uint32_t a1, uint32_t a2, uint32_t a3, uint32_t db) {
  asm volatile("{\n.reg .pred p;\n.reg .b64 db;\nsetp.ne.b32 p, 0, 0;\nmov.b64 db, {%24, %26};\n"
    "wgmma.mma_async.sync.aligned.m64n40k16.f32.bf16.bf16 {%0, %1, %2, %3, %4, %5, %6, %7, %8, %9, %10, %11, %12, %13, %14, %15, %16, %17, %18, %19}, {%20, %21, %22, %23}, db, p, 1, 1, %25;\n}\n"
    : "=f"(d[0]), "=f"(d[1]), "=f"(d[2]), "=f"(d[3]), "=f"(d[4]), "=f"(d[5]), "=f"(d[6]), "=f"(d[7]), "=f"(d[8]), "=f"(d[9]), "=f"(d[10]), "=f"(d[11]), "=f"(d[12]), "=f"(d[13]), "=f"(d[14]), "=f"(d[15]), "=f"(d[16]), "=f"(d[17]), "=f"(d[18]), "=f"(d[19])
    : "r"(a0), "r"(a1), "r"(a2), "r"(a3), "r"(db), "n"(TB), "n"(HI));
}
template<int TB, uint32_t HI> __device__ __forceinline__ void wgmma_rs_n32(float (&d)[16], uint32_t a0, uint32_t a1, uint32_t a2, uint32_t a3, uint32_t db) {
  asm volatile("{\n.reg .pred p;\n.reg .b64 db;\nsetp.ne.b32 p, 1, 0;\nmov.b64 db, {%20, %22};\n"
    "wgmma.mma_async.sync.aligned.m64n32k16.f32.bf16.bf16 {%0, %1, %2, %3, %4, %5, %6, %7, %8, %9, %10, %11, %12, %13, %14, %15}, {%16, %17, %18, %19}, db, p, 1, 1, %21;\n}\n"
    : "+f"(d[0]), "+f"(d[1]), "+f"(d[2]), "+f"(d[3]), "+f"(d[4]), "+f"(d[5]), "+f"(d[6]), "+f"(d[7]), "+f"(d[8]), "+f"(d[9]), "+f"(d[10]), "+f"(d[11]), "+f"(d[12]), "+f"(d[13]), "+f"(d[14]), "+f"(d[15])
    : "r"(a0), "r"(a1), "r"(a2), "r"(a3), "r"(db), "n"(TB), "n"(HI));
}
template<int TB, uint32_t HI> __device__ __forceinline__ void wgmma_rsz_n32(float (&d)[16], uint32_t a0, uint32_t a1, uint32_t a2, uint32_t a3, uint32_t db) {
  asm volatile("{\n.reg .pred p;\n.reg .b64 db;\nsetp.ne.b32 p, 0, 0;\nmov.b64 db, {%20, %22};\n"
    "wgmma.mma_async.sync.aligned.m64n32k16.f32.bf16.bf16 {%0, %1, %2, %3, %4, %5, %6, %7, %8, %9, %10, %11, %12, %13, %14, %15}, {%16, %17, %18, %19}, db, p, 1, 1, %21;\n}\n"
    : "=f"(d[0]), "=f"(d[1]), "=f"(d[2]), "=f"(d[3]), "=f"(d[4]), "=f"(d[5]), "=f"(d[6]), "=f"(d[7]), "=f"(d[8]), "=f"(d[9]), "=f"(d[10]), "=f"(d[11]), "=f"(d[12]), "=f"(d[13]), "=f"(d[14]), "=f"(d[15])
    : "r"(a0), "r"(a1), "r"(a2), "r"(a3), "r"(db), "n"(TB), "n"(HI));
}

__device__ __forceinline__ void phi_mma(float (&d)[16], const uint32_t* a, uint32_t wphi) {
  wgmma_rsz_n32<1, H64>(d, a[0], a[1], a[2], a[3], desc_lo(wphi, 2048));
  wgmma_rs_n32<1, H64>(d, a[4], a[5], a[6], a[7], desc_lo(wphi + 1024, 2048));
}

constexpr int NJOBS = 7;
constexpr int NST = 16 * 6 + 56;
constexpr int J_Q = 16, J_WO = 32, J_F1 = 48, J_F1A = 64, J_F2 = 96;
struct Sched { int off[NST]; int need[NST]; };
constexpr int JSZ[NJOBS] = {6, 4, 4, 5, 4, 4, 4};
constexpr Sched make_sched() {
  Sched s{};
  int off = 0;
  for (int g = 0; g < NST; g++) {
    int j = g < J_F2 ? g / 16 : 6, sz = JSZ[j];
    if (off + sz > 24) off = 0;
    if ((j == 1 || g == J_WO) && off == 4) off = 8;
    s.off[g] = off;
    int need = g - 8;
    for (int p = g - 1; p >= 0 && p > g - 8; p--)
      if (s.off[p] < off + sz && off < s.off[p] + JSZ[p < J_F2 ? p / 16 : 6]) { need = p; break; }
    s.need[g] = need;
    off += sz;
  }
  return s;
}
constexpr Sched SCH = make_sched();
static_assert(SCH.off[J_WO] == 8 && SCH.off[J_WO + 3] == 20 && SCH.off[J_WO + 5] == 4 && SCH.off[J_F1] == 0 && SCH.off[J_F1 + 3] == 15 &&
              SCH.off[J_F1 + 4] == 0 && SCH.off[12] == 0 && SCH.off[13] == 6, "schedule");
constexpr int LAST_REL = SCH.need[NST - 1];
template<int G> constexpr uint32_t OFF = SCH.off[G] * 8192;
template<int G> constexpr int NEED = SCH.need[G];
constexpr int NREC = 160;
struct Tab { uint32_t a[8][NREC][2]; uint32_t b[8][NREC]; };
constexpr uint32_t wt_empty(int g) { return (8 + (g & 7)) << 3 | ((g >> 3) & 1); }
constexpr uint32_t WT_GS1 = 20 << 3, WT_SCR = 16 << 3, WT_KV = 21 << 3, WT_T0 = 22 << 3;
constexpr int NA = NST - 8 + 9;
constexpr Tab make_tab() {
  Tab t{};
  for (int n = 0; n < 8; n++) {
    int na = 0;
    for (int g = 0; g < NST; g++) {
      const int j = g < J_F2 ? g / 16 : 6, i = g - j * 16, rank = n & 1;
      const bool own = j == 2 || j == 3;
      int k = i;
      if (own) {
        if (i < 4) k = 2 * (n ^ (i & 1)) + (i >> 1);
        else { int odd = i >= 10; k = 2 * (((n & 6) + 2 + i - 4 - odd * 6) & 7) + odd; }
      }
      const int tx = JSZ[j] - (own && (i == 0 || i == 2) ? 2 : 0);
      t.b[n][g] = (g == 3 ? WT_GS1 : g == J_WO + 5 ? WT_SCR : wt_empty(SCH.need[g])) | tx << 8 | SCH.off[g] << 13 | j << 18 | k << 21 | (j == 3 ? 3 * n : 2 * n) << 27;
      int need = SCH.need[g], tile = k, line = 0; uint32_t want = 0;
      const int R = j == 2 ? 6 : 4;
      if (j == 1) { line = rank; want = 0xFu << ((i >> 1) * 4); }
      else if (own) {
        const uint32_t pm = 5u << ((n & 6) * 2);
        tile = (j - 1) * 16 + k; line = j; want = (1u << k) | (i >= R ? pm : 0u) | (i >= R + 2 ? pm * 2 : 0u);
        if (i == R && need < g - R + 1) need = g - R + 1;
        if (i == R + 2 && need < g - R + 1) need = g - R + 1;
      } else if (j == 6) {
        tile = 48 + i; line = 4 + rank + (i < 24 ? 0 : i < 40 ? 2 : 4); want = 0xFu << ((i < 24 ? i / 3 : ((i - 24) & 15) >> 1) * 4);
      } else if (j > 3) { tile = 32 + i; line = 3; }
      if (g == J_WO) t.a[n][na++][1] = WT_KV | line << 25 | 4u << 29;
      if (own && i < 4) {
        if (i & 1) t.a[n][na++][1] = (WT_T0 + (i >> 1) * 8 + j - 2) | (g & 7) << 8 | SCH.off[g - 1] << 13 | ((j - 1) * 16 + 2 * n + (i >> 1)) << 18 | line << 25 | 2u << 29;
        for (int e = 0; e < 2 && i == 3; e++) t.a[n][na++][1] = (WT_T0 + j - 2) | ((j - 1) * 16 + 2 * n + e) << 18 | line << 25 | 3u << 29;
      } else {
        t.a[n][na][0] = want;
        t.a[n][na++][1] = (g == 3 ? WT_GS1 : g == J_WO + 5 ? WT_SCR : wt_empty(need)) | (g & 7) << 8 | SCH.off[g] << 13 | tile << 18 | line << 25 | (j == 0 ? 1u : 0u) << 29;
      }
    }
    if (na != NA) t.b[n][NREC] = 0;
  }
  return t;
}
__device__ const Tab g_tab = make_tab();

constexpr uint32_t SM_RING = 192 * 1024;
constexpr uint32_t SM_SCR = 32 * 1024;
constexpr uint32_t SM_MISC = SM_RING;
constexpr uint32_t SM_WPHI = SM_MISC;
constexpr uint32_t SM_STG = SM_MISC + 8192;
constexpr uint32_t SM_GS1 = SM_MISC + 24576;
constexpr uint32_t SM_GS2 = SM_MISC + 28672;
constexpr uint32_t SM_VEC = SM_MISC + 32768;
constexpr uint32_t SM_BAR = SM_MISC + 34816;
constexpr uint32_t SM_TOTAL = SM_MISC + 35840;
constexpr uint32_t B_FULL = SM_BAR, B_EMPTY = SM_BAR + 64, B_SCR = SM_BAR + 128, B_WPHI = SM_BAR + 136, B_VEC = SM_BAR + 144,
                   B_UT = SM_BAR + 152, B_GS1 = SM_BAR + 160, B_KV = SM_BAR + 168, B_T0 = SM_BAR + 176, B_G = SM_BAR + 192, B_PW = SM_BAR + 224, B_PX = SM_BAR + 232;
constexpr uint32_t SM_PW = 18 * 8192, SM_PX = SM_RING - 16384;

struct Params {
  CUtensorMap tm_b[NJOBS], tm_x, tm_out, tm_wphi, tm_g[2], tm_p[2];
  const bf16 *x, *wqkv, *wo, *w1, *w2, *b1, *b2, *c, *wmod;
};

__device__ __forceinline__ float silu_bf(float v) { return bf_round(__fdividef(v, 1.f + __expf(-v))); }
__device__ __forceinline__ void wait_empty(uint32_t sb, int g) { mbar_wait(sb + B_EMPTY + 8 * (g & 7), (g >> 3) & 1); }

template<int SZ, bool SKIP> __device__ __forceinline__ uint32_t next_slot(uint32_t a, uint32_t sb) {
  a += SZ * 8192;
  if (a == sb + (24 / SZ) * SZ * 8192) a = sb;
  if (SKIP && a == sb + SM_SCR) a += 32768;
  return a;
}

struct Ctx { uint32_t sb, ebase, stg, srow; int wg, tid, lane, w4; uint32_t epoch; };
struct Pipe { uint32_t g, a; };

__device__ __forceinline__ void release_stage(const Ctx& c, uint32_t g) { if (c.tid < 2) mbar_arrive_cl(c.ebase + 8 * (g & 7)); }
__device__ __forceinline__ void wait_full(const Ctx& c, const Pipe& p) { mbar_wait(c.sb + B_FULL + 8 * (p.g & 7), (p.g >> 3) & 1); }
template<int N, int Z> __device__ __forceinline__ void mma4(const Ctx& c, float (&acc)[N / 2], const Pipe& p, uint32_t sd = 1) {
  uint32_t da = desc_lo(p.a + c.wg * 8192, 0), db = desc_lo(p.a + 16384, 8192);
#pragma unroll
  for (int k = 0; k < 4; k++) {
    if constexpr (N == 192) { if (Z && k == 0) wgmma_ssz_n192<0, 1, H128>(acc, da, db); else wgmma_ss_n192<0, 1, H128>(acc, da + k * 2, db + k * 128); }
    else { if (Z && k == 0) wgmma_ssp_n128<0, 1, H128>(acc, da, db, sd); else wgmma_ss_n128<0, 1, H128>(acc, da + k * 2, db + k * 128); }
  }
}
template<int N, bool SKIP> __device__ __forceinline__ void step(const Ctx& c, Pipe& p, float (&acc)[N / 2]) {
  wait_full(c, p);
  wgmma_fence();
  mma4<N, 0>(c, acc, p);
  wgmma_commit();
  wgmma_wait<1>();
  release_stage(c, p.g - 1);
  p.g++; p.a = next_slot<N == 192 ? 5 : 4, SKIP>(p.a, c.sb);
}

template<int R0 = 0, int R1 = 2> __device__ __forceinline__ void dual_softmax(const float* p, uint32_t (&ph)[16]) {
  constexpr float L2E = 1.4426950408889634f;
#pragma unroll
  for (int r = R0; r < R1; r++) {
    float mx = fmaxf(p[2 * r], p[2 * r + 1]), mn = fminf(p[2 * r], p[2 * r + 1]);
#pragma unroll
    for (int j = 1; j < 4; j++) { mx = fmaxf(mx, fmaxf(p[4 * j + 2 * r], p[4 * j + 2 * r + 1])); mn = fminf(mn, fminf(p[4 * j + 2 * r], p[4 * j + 2 * r + 1])); }
    mx = fmaxf(mx, __shfl_xor_sync(~0u, mx, 1)); mn = fminf(mn, __shfl_xor_sync(~0u, mn, 1));
    mx = fmaxf(mx, __shfl_xor_sync(~0u, mx, 2)); mn = fminf(mn, __shfl_xor_sync(~0u, mn, 2));
    float a = -mx * L2E, b = mn * L2E;
    float ep[8], en[8], sp = 0.f, sn = 0.f;
#pragma unroll
    for (int j = 0; j < 4; j++)
#pragma unroll
      for (int e = 0; e < 2; e++) {
        float v = p[4 * j + 2 * r + e];
        ep[2 * j + e] = ex2(fmaf(v, L2E, a)); en[2 * j + e] = ex2(fmaf(v, -L2E, b));
        sp += ep[2 * j + e]; sn += en[2 * j + e];
      }
    sp += __shfl_xor_sync(~0u, sp, 1); sn += __shfl_xor_sync(~0u, sn, 1);
    sp += __shfl_xor_sync(~0u, sp, 2); sn += __shfl_xor_sync(~0u, sn, 2);
    float ip = rcp(sp), in = rcp(sn);
#pragma unroll
    for (int j = 0; j < 4; j++) {
      ph[2 * j + r] = pack_bf16(ep[2 * j] * ip, ep[2 * j + 1] * ip);
      ph[8 + 2 * j + r] = pack_bf16(en[2 * j] * in, en[2 * j + 1] * in);
    }
  }
}
__device__ __forceinline__ void row_stats(const uint32_t (&v)[32], int lane, float& s0, float& s1, float& q0, float& q1) {
  float ds[4] = {0.f, 0.f, 0.f, 0.f}, d0[4] = {0.f, 0.f, 0.f, 0.f}, d1[4] = {0.f, 0.f, 0.f, 0.f};
#pragma unroll
  for (int k = 0; k < 8; k++) {
    hmma(ds, v[4 * k], v[4 * k + 1], v[4 * k + 2], v[4 * k + 3], 0x3f803f80u, 0x3f803f80u);
    hmma(d0, v[4 * k], v[4 * k + 1], v[4 * k + 2], v[4 * k + 3], v[4 * k], v[4 * k + 2]);
    hmma(d1, v[4 * k], v[4 * k + 1], v[4 * k + 2], v[4 * k + 3], v[4 * k + 1], v[4 * k + 3]);
  }
  s0 = ds[0]; s1 = ds[2]; q0 = (lane & 4) ? d0[1] : d0[0]; q1 = (lane & 4) ? d1[3] : d1[2];
}

__device__ __forceinline__ uint32_t stm_addr(const Ctx& c, uint32_t base, int cb) { return base + (c.srow ^ (cb << 4)); }

__device__ __forceinline__ void stg_acquire(const Ctx& c) { if (c.lane == 0) bulk_wait_read0(); __syncwarp(); }
__device__ __forceinline__ void stg_store(const Ctx& c, uint8_t* dst) {
  fence_async_smem();
  __syncwarp();
  if (c.lane == 0) { bulk_store(dst, c.stg, 2048); bulk_commit(); }
}
__device__ __forceinline__ void warp_publish(const Ctx& c, uint32_t* flag) { if (c.lane == 0) { bulk_wait0(); st_relaxed(flag, c.epoch); } __syncwarp(); }

__device__ __forceinline__ uint4 poll4(const void* p, uint32_t epoch) {
  uint4 v; uint32_t n = 0;
  do { v = ld_vol4(p); spin_guard(++n); } while (v.y != epoch || v.w != epoch);
  return v;
}
__device__ __forceinline__ void poll4x2(const void* p0, const void* p1, uint32_t epoch, uint4& v, uint4& w) {
  uint32_t n = 0;
  do { v = ld_vol4(p0); w = ld_vol4(p1); spin_guard(++n); } while (v.y != epoch || v.w != epoch || w.y != epoch || w.w != epoch);
}
__device__ __forceinline__ void poll_flags(const uint32_t* flags, int lane, uint32_t epoch, uint32_t want, uint32_t& mask) {
  uint32_t it = 0;
  while ((mask & want) != want) {
    mask = __ballot_sync(~0u, ld_relaxed(flags + lane) == epoch);
    spin_guard(++it);
  }
}

__global__ void __cluster_dims__(2, 1, 1) __launch_bounds__(384, 1) mega_kernel(const __grid_constant__ Params p) {
  extern __shared__ __align__(1024) uint8_t smem_raw[];
  uint32_t sb = smem_u32(smem_raw);
  asm volatile("" : "+r"(sb));
  const int tid = threadIdx.x, lane = tid & 31, warp = __shfl_sync(~0u, tid >> 5, 0), wg = warp >> 2;
  const int b = blockIdx.x, m = b >> 3, n = b & 7, rank = b & 1;
  uint8_t* const act = g_act + (size_t)m * 104 * 16384;
  uint32_t* const flg = g_flag + m * 320;

  if (wg == 2) {
    if (warp == 8) {
      if (lane == 0) {
        mbar_init(sb + B_PW, 1); mbar_init(sb + B_PX, 1);
        asm volatile("fence.mbarrier_init.release.cluster;" ::: "memory");
        tma_load_3d(sb + SM_PW, &p.tm_p[0], sb + B_PW, b * 16, 0);
        tma_load_3d(sb + SM_PX, &p.tm_p[1], sb + B_PX, 0, b * 16);
        mbar_expect_tx(sb + B_PW, 32768); mbar_expect_tx(sb + B_PX, 32768);
      }
      __syncwarp();
      spin_guard((sb & 1023) ? ~0u : 0u);
      if (lane == 0) TL(31);
      bar_arrive(5, 288);
    }
    if (tid == 288) {
#pragma unroll
      for (int i = 0; i < 28; i++) mbar_init(sb + SM_BAR + 8 * i, i < 8 ? 1u : i < 16 ? 4u : 1u << ((0x11316602ull >> (4 * (i - 16))) & 15));
      asm volatile("fence.mbarrier_init.release.cluster;" ::: "memory");
    }
    if (tid == 320) { prefetch_tmap(&p.tm_b[0]); prefetch_tmap(&p.tm_x); }
    __syncwarp();
    cluster_arrive();
    reg_dealloc<56>();
    if (tid == 256) TL(32);
    const uint32_t epoch = ld_relaxed(&g_epoch) + 1;
    if (warp == 8) {
      uint32_t rec[5];
#pragma unroll
      for (int i = 0; i < 5; i++) rec[i] = ld_nc1(&g_tab.b[n][i * 32 + lane]);
      uint32_t wn = __shfl_sync(~0u, rec[0], 0);
      cluster_wait();
#pragma unroll 1
      for (int g = 0; g < NST; g++) {
        const uint32_t w = wn;
        if ((g & 31) == 31) { rec[0] = rec[1]; rec[1] = rec[2]; rec[2] = rec[3]; rec[3] = rec[4]; }
        wn = __shfl_sync(~0u, rec[0], g + 1);
        asm volatile("{\n.reg .pred p;\n.reg .b32 n, a;\n" MBAR_WAIT("%0", "%1", "%2") "elect.sync _|p, 0xffffffff;\n"
          "@p mbarrier.arrive.expect_tx.shared::cta.b64 _, [%3], %4;\n"
          "@p cp.async.bulk.tensor.4d.shared::cluster.global.mbarrier::complete_tx::bytes [%5], [%6, {%9, %7, %8, %9}], [%3];\n}\n"
          :: "r"(sb + SM_BAR + (w & 0xF8)), "r"(w & 1), "n"(SPIN_LIMIT), "r"(sb + B_FULL + 8 * (g & 7)), "r"((w << 5) & 0xE000),
             "r"(sb + 16384 + (w & 0x3E000)), "l"(&p.tm_b[(w >> 18) & 7]), "r"((w >> 15) & 0xFC0), "r"(w >> 27), "r"(0) : "memory");
      }
    } else if (warp == 9) {
      uint2 rec[5];
#pragma unroll
      for (int i = 0; i < 5; i++) rec[i] = ld_nc2(&g_tab.a[n][i * 32 + lane][0]);
      uint32_t mask = 0, line = 0, wn = __shfl_sync(~0u, rec[0].y, 0), wantn = 0;
      const uint8_t* asrc = act + rank * 8192;
      cluster_wait();
#pragma unroll 1
      for (int g = 0; g < NA; g++) {
        const uint32_t w = wn, want = wantn;
        if ((g & 31) == 31) { rec[0] = rec[1]; rec[1] = rec[2]; rec[2] = rec[3]; rec[3] = rec[4]; }
        wn = __shfl_sync(~0u, rec[0].y, g + 1); wantn = __shfl_sync(~0u, rec[0].x, g + 1);
        if (((w >> 25) & 15) != line) { line = (w >> 25) & 15; mask = 0; }
        poll_flags(flg + line * 32, lane, epoch, want, mask);
        const uint32_t bar = sb + B_FULL + ((w >> 5) & 0x38), dst = sb + (w & 0x3E000), tile = (w >> 18) & 127;
        asm volatile("{\n.reg .pred p;\n.reg .b32 n, a;\n" MBAR_WAIT("%0", "%1", "%2") "elect.sync _|p, 0xffffffff;\nsetp.lt.and.u32 p, %6, 0x20000000, p;\n"
          "@p cp.async.bulk.shared::cluster.global.mbarrier::complete_tx::bytes.multicast::cluster [%4], [%5], 8192, [%3], %7;\n}\n"
          :: "r"(sb + SM_BAR + (w & 0xF8)), "r"(w & 1), "n"(SPIN_LIMIT), "r"(bar), "r"(dst + rank * 8192), "l"(asrc + tile * 16384), "r"(w), "h"((uint16_t)3) : "memory");
        if (w >> 29) {
          if (lane == 0) {
            if ((w >> 29) == 1) tma_load_2d_mc(dst + rank * 8192, &p.tm_x, bar, g * 64, m * 128 + rank * 64, 3);
            else if ((w >> 29) == 2) {
              bulk_store(act + tile * 16384, dst, 16384); bulk_commit();
              bulk_copy_peer(mapa(dst + 32768 + (w & 1) * 8192, rank ^ 1), dst, 16384, mapa(bar, rank ^ 1));
            } else {
              uint32_t* f = flg + line * 32 + (tile & 15);
              if ((w >> 29) == 3) { if (tile & 1) bulk_wait0(); else bulk_wait1(); TL(40 + 2 * (w & 1) + (tile & 1)); }
              else { TL(52); __threadfence(); f = &g_kvflag[n * 32 + m]; TL(53); }
              st_relaxed(f, epoch);
            }
          }
          __syncwarp();
        }
      }
    } else {
      const int ht = tid - 320;
      cluster_wait();
      mbar_wait(sb + B_GS1, 0);
      if (ht == 63) { mbar_expect_tx(sb + B_WPHI, 8192); tma_load_2d(sb + SM_WPHI, &p.tm_wphi, sb + B_WPHI, 0, n * 128); }
      const int nbox = b < 112 ? 32 : 16;
      auto box = [&](int u) {
        mbar_expect_tx(sb + B_G + 8 * (u & 3), 4096);
        tma_load_2d(sb + SM_STG + (u & 3) * 4096, &p.tm_g[u >> 4], sb + B_G + 8 * (u & 3), b * 32, (u & 15) * 64);
      };
      if (ht < 4) box(ht);
#pragma unroll 1
      for (int pass = 0; pass < 2; pass++) {
        bar_sync(4, 64);
        if (pass * 16 < nbox) {
          float d[4][4] = {};
          const uint32_t wa = sb + SM_STG + ((lane & 7) + (lane >> 4) * 8) * 64 + (((((lane >> 3) & 1) + (ht >> 5) * 2) ^ ((lane & 7) >> 1)) << 4);
#pragma unroll 1
          for (int t = 0; t < 16; t++) {
            uint4 cf[2];
#pragma unroll
            for (int i = 0; i < 2; i++) cf[i] = lds4(sb + SM_GS2 + t * 256 + i * 128 + (lane & 7) * 16);
            mbar_wait(sb + B_G + 8 * (t & 3), (t >> 2) & 1);
            uint32_t a[16];
#pragma unroll
            for (int i = 0; i < 4; i++) ldmatrix_x4t(wa + (t & 3) * 4096 + i * 1024, a[4 * i], a[4 * i + 1], a[4 * i + 2], a[4 * i + 3]);
            asm volatile("" :: "r"(a[0]), "r"(a[4]), "r"(a[8]), "r"(a[12]), "r"(cf[0].x), "r"(cf[1].x) : "memory");
            bar_sync(4, 64);
            if (ht == 0 && pass * 16 + t + 4 < nbox) box(pass * 16 + t + 4);
#pragma unroll
            for (int i = 0; i < 4; i++) hmma(d[i], a[4 * i], a[4 * i + 1], a[4 * i + 2], a[4 * i + 3], (i & 1) ? cf[i >> 1].z : cf[i >> 1].x, (i & 1) ? cf[i >> 1].w : cf[i >> 1].y);
          }
          const int col = b * 32 + (ht >> 5) * 16 + (lane & 1) * 8 + (lane >> 2);
#pragma unroll
          for (int e = 0; e < 4; e++) d[0][e] = (d[0][e] + d[1][e]) + (d[2][e] + d[3][e]);
          float o0 = (lane & 1) ? d[0][2] : d[0][0], o1 = (lane & 1) ? d[0][3] : d[0][1];
          float nb = __shfl_down_sync(~0u, o0, 4);
          if (pass) { if (!(lane & 2)) st_vol4(&g_utpk[col], __float_as_uint(o0), epoch, __float_as_uint(o1 + __bfloat162float(p.b1[col])), epoch); }
          else if (!(lane & 6)) st_vol2(&g_modpk[1024 + (col >> 1)], pack_bf16(o0, nb), epoch);
        }
        if (ht == 0) TL(48 + 2 * pass);
        if (pass) break;
        if (ht == 8) bulk_prefetch(p.wo + (size_t)b * 8192, 16384);
#pragma unroll 1
        for (int i = ht; i < 256; i += 64) {
          uint4 s, cc;
          poll4x2(&g_modpk[1536 + 2 * i], &g_modpk[2048 + 2 * i], epoch, s, cc);
          const uint32_t c0 = pack_bf16(1.f + bf_lo(cc.x), 1.f + bf_hi(cc.x)), c1 = pack_bf16(1.f + bf_lo(cc.z), 1.f + bf_hi(cc.z));
          const uint32_t ca = sb + SM_GS2 + (i >> 3) * 128 + (i & 1) * 32 + (i & 6) * 2;
          sts1(ca, c0); sts1(ca + 16, c1); sts1(ca + 64, s.x); sts1(ca + 80, s.z);
          if ((i >> 5) == n) { sts1(sb + SM_VEC + lane * 32 + 4, c0); sts1(sb + SM_VEC + lane * 32 + 20, c1); }
        }
        {
          uint4 gv = poll4(&g_modpk[1024 + (ht >> 5) * 1536 + n * 64 + lane * 2], epoch);
          sts1(sb + SM_VEC + lane * 32 + (ht >> 5) * 8, gv.x); sts1(sb + SM_VEC + lane * 32 + 16 + (ht >> 5) * 8, gv.z);
          sts1(sb + SM_VEC + ht * 16 + 12, ld_nc1(p.b2 + n * 128 + 2 * ht));
        }
        mbar_arrive(sb + B_VEC);
        if (ht == 0) TL(49);
      }
      if (ht < 8) bulk_prefetch(p.w2 + (size_t)(b * 8 + ht) * FF, FF * 2);
#pragma unroll 1
      for (int i = ht; i < 160; i += 64) g_kvacc[(epoch + 1) & 1][b * 160 + i] = make_float4(0.f, 0.f, 0.f, 0.f);
      mbar_wait(sb + B_KV, 0);
      if (ht == 0) { uint32_t t = atomicInc(&g_done, 127); if (t == 127) g_epoch = epoch; }
      {
        uint4 v[7];
        uint32_t it = 0, bad;
        do {
          bad = 0;
#pragma unroll
          for (int i = 0; i < 7; i++) v[i] = ld_vol4(&g_utpk[(i < 3 ? n * 192 : n * 128 + (i < 5 ? 1344 : 2240)) + i * 64 + ht]);
#pragma unroll
          for (int i = 0; i < 7; i++) bad |= (v[i].y ^ epoch) | (v[i].w ^ epoch);
          spin_guard(++it);
        } while (bad);
#pragma unroll
        for (int i = 0; i < 7; i++) sts2(sb + SM_GS1 + (i * 64 + ht) * 8, v[i].x, v[i].z);
      }
      mbar_arrive(sb + B_UT);
      if (ht == 0) TL(51);
    }
  } else {
    const int q = lane & 3;
    const int r0 = m * 128 + wg * 64 + (warp & 3) * 16 + (lane >> 2);
    Ctx c;
    float rs0, nm0, rs1, nm1;
    {
      const uint2 cv = ld_nc2(p.c + 4 * tid);
      const uint32_t epoch = ld_relaxed(&g_epoch) + 1;
      cluster_arrive();
      const uint32_t ca = sb + SM_GS2 + (tid >> 3) * 128 + (tid & 1) * 32 + (tid & 6) * 2;
      sts1(ca, pack_bf16(silu_bf(bf_lo(cv.x)), silu_bf(bf_hi(cv.x)))); sts1(ca + 16, pack_bf16(silu_bf(bf_lo(cv.y)), silu_bf(bf_hi(cv.y))));
      reg_alloc<224>();
      c.sb = sb; c.wg = wg; c.tid = tid & 127; c.lane = lane; c.w4 = warp & 3; c.epoch = epoch;
      c.ebase = mapa(sb + B_EMPTY, tid & 1); c.stg = sb + SM_STG + warp * 2048;
      c.srow = (lane & 15) * 128 + (((lane >> 4) ^ (lane & 7)) << 4);
      bar_sync(5, 288);
      uint4 cf[4];
#pragma unroll
      for (int i = 0; i < 4; i++) cf[i] = lds4(sb + SM_GS2 + (warp * 4 + i) * 128 + q * 16);
      uint32_t xv[32];
      float d[2][4] = {};
      mbar_wait(sb + B_PW, 0);
#pragma unroll
      for (int i = 0; i < 8; i++) {
        ldmatrix_x4t(sb + SM_PW + warp * 4096 + i * 512 + ((lane & 7) + (lane >> 4) * 8) * 32 + (((lane >> 3) ^ (lane >> 2)) & 1) * 16, xv[0], xv[1], xv[2], xv[3]);
        hmma(d[i & 1], xv[0], xv[1], xv[2], xv[3], (i & 1) ? cf[i >> 1].z : cf[i >> 1].x, (i & 1) ? cf[i >> 1].w : cf[i >> 1].y);
      }
      const uint32_t red = sb + SM_VEC + warp * 256;
      if (q < 2) sts1(red + q * 32 + (lane >> 2) * 4, __float_as_uint(q ? d[0][2] + d[1][2] : d[0][0] + d[1][0]));
      mbar_wait(sb + B_PX, 0);
#pragma unroll
      for (int i = 0; i < 8; i++) ldmatrix_x4(stm_addr(c, sb + SM_PX + warp * 4096 + (i >> 2) * 2048, (i & 3) * 2), xv[4 * i], xv[4 * i + 1], xv[4 * i + 2], xv[4 * i + 3]);
      float s0, s1, q0, q1;
      row_stats(xv, lane, s0, s1, q0, q1);
      if (q == (lane >> 3)) { sts2(red + 64 + (lane >> 2) * 8, __float_as_uint(s0), __float_as_uint(q0)); sts2(red + 128 + (lane >> 2) * 8, __float_as_uint(s1), __float_as_uint(q1)); }
      bar_sync(3, 256);
      if (tid < 24) {
        s0 = 0.f; s1 = 0.f;
#pragma unroll
        for (int w = 0; w < 8; w++) { uint2 v = lds2(sb + SM_VEC + w * 256 + tid * 8); s0 += __uint_as_float(v.x); s1 += __uint_as_float(v.y); }
        if (tid < 8) {
#pragma unroll
          for (int i = 0; i < 8; i++) st_vol2(&g_modpk[(i ? 2048 + 1024 * i : 0) + b * 8 + tid], pack_bf16(s0, s1), epoch);
        }
        else {
          s0 *= (1.f / DM);
          float rs = rsqrtf(fmaxf(fmaf(s1, 1.f / DM, -s0 * s0), 0.f) + 1e-5f);
          st_vol4(&g_st1pk[b * 16 + tid - 8], __float_as_uint(rs), epoch, __float_as_uint(-s0 * rs), epoch);
        }
      }
      if (tid == 0) TL(1);
      cluster_wait();
      {
        const uint2* mp = &g_modpk[(n ? 2048 + 1024 * n : 0) + 2 * tid];
        uint4 sv, cc, t0, t1;
        uint32_t it = 0;
        do {
          sv = ld_vol4(mp); cc = ld_vol4(mp + 512); t0 = ld_vol4(&g_st1pk[r0]); t1 = ld_vol4(&g_st1pk[r0 + 8]);
          spin_guard(++it);
        } while (((sv.y ^ epoch) | (sv.w ^ epoch) | (cc.y ^ epoch) | (cc.w ^ epoch) | (t0.y ^ epoch) | (t0.w ^ epoch) | (t1.y ^ epoch) | (t1.w ^ epoch)) != 0);
        uint32_t ad = sb + SM_GS1 + (tid >> 2) * 64 + (tid & 1) * 32 + ((tid >> 1) & 1) * 4;
        sts1(ad, pack_bf16(1.f + bf_lo(cc.x), 1.f + bf_hi(cc.x))); sts1(ad + 8, sv.x);
        sts1(ad + 16, pack_bf16(1.f + bf_lo(cc.z), 1.f + bf_hi(cc.z))); sts1(ad + 24, sv.z);
          rs0 = __uint_as_float(t0.x); nm0 = __uint_as_float(t0.z); rs1 = __uint_as_float(t1.x); nm1 = __uint_as_float(t1.z);
      }
      bar_sync(3, 256);
      if (tid < 2) mbar_arrive_cl(c.ebase + (B_GS1 - B_EMPTY));
      if (tid == 0) TL(2);
    }
    const uint32_t epoch = c.epoch;
    const uint32_t wrow = wg * 8192 + c.w4 * 2048;
    uint32_t* const wflag = flg + wg * 32 + n * 4 + c.w4;
    Pipe pp;
    float accq[64];
    {
      float acc[128];
      uint32_t A[16];
      zero_regs(acc);
      pp.g = 0; pp.a = sb;
#pragma unroll 1
      do {
        uint32_t T[16];
        wait_full(c, pp);
#pragma unroll
        for (int k = 0; k < 4; k++) {
          ldmatrix_x4(stm_addr(c, pp.a + wrow, 2 * k), T[4 * k], T[4 * k + 1], T[4 * k + 2], T[4 * k + 3]);
          T[4 * k] = pack_bf16(fmaf(bf_lo(T[4 * k]), rs0, nm0), fmaf(bf_hi(T[4 * k]), rs0, nm0));
          T[4 * k + 1] = pack_bf16(fmaf(bf_lo(T[4 * k + 1]), rs1, nm1), fmaf(bf_hi(T[4 * k + 1]), rs1, nm1));
          T[4 * k + 2] = pack_bf16(fmaf(bf_lo(T[4 * k + 2]), rs0, nm0), fmaf(bf_hi(T[4 * k + 2]), rs0, nm0));
          T[4 * k + 3] = pack_bf16(fmaf(bf_lo(T[4 * k + 3]), rs1, nm1), fmaf(bf_hi(T[4 * k + 3]), rs1, nm1));
        }
        uint4 gs[4];
#pragma unroll
        for (int k = 0; k < 4; k++) gs[k] = lds4(sb + SM_GS1 + (pp.g * 4 + k) * 64 + q * 16);
        wgmma_wait<0>();
#pragma unroll
        for (int k = 0; k < 4; k++) {
          asm volatile("fma.rn.bf16x2 %0, %1, %2, %3;" : "=r"(A[4 * k]) : "r"(T[4 * k]), "r"(gs[k].x), "r"(gs[k].z));
          asm volatile("fma.rn.bf16x2 %0, %1, %2, %3;" : "=r"(A[4 * k + 1]) : "r"(T[4 * k + 1]), "r"(gs[k].x), "r"(gs[k].z));
          asm volatile("fma.rn.bf16x2 %0, %1, %2, %3;" : "=r"(A[4 * k + 2]) : "r"(T[4 * k + 2]), "r"(gs[k].y), "r"(gs[k].w));
          asm volatile("fma.rn.bf16x2 %0, %1, %2, %3;" : "=r"(A[4 * k + 3]) : "r"(T[4 * k + 3]), "r"(gs[k].y), "r"(gs[k].w));
        }
        uint32_t db = desc_lo(pp.a + 16384, 8192);
        wgmma_fence();
#pragma unroll
        for (int k = 0; k < 4; k++) wgmma_rs_n256<1, H128>(acc, A[4 * k], A[4 * k + 1], A[4 * k + 2], A[4 * k + 3], db + k * 128);
        wgmma_commit();
        if ((int)(pp.g - 1) >> 1 == n) { if (lane == 0) bulk_wait_read0(); bar_sync(1 + wg, 128); }
        if (pp.g) release_stage(c, pp.g - 1);
        if ((int)(pp.g >> 1) == n) {
#pragma unroll
          for (int k = 0; k < 4; k++) stmatrix_x4(stm_addr(c, pp.a + wrow, 2 * k), A[4 * k], A[4 * k + 1], A[4 * k + 2], A[4 * k + 3]);
          fence_async_smem();
          __syncwarp();
          if (lane == 0) { bulk_store(act + pp.g * 16384 + wrow, pp.a + wrow, 2048); bulk_commit(); }
        }
        if ((int)pp.g == min(2 * n + 2, 15)) warp_publish(c, wflag);
        pp.g++; pp.a = next_slot<6, false>(pp.a, sb);
      } while (pp.g < J_Q);
      bar_sync(1 + wg, 128);
      wgmma_wait<0>();
      fence_regs(acc);
      if (tid == 0) TL(4);
      pp.a = sb + OFF<J_Q>;
      {
        uint32_t kp[32], vp[32];
#pragma unroll
        for (int i = 0; i < 32; i++) {
          asm volatile("cvt.rn.bf16x2.f32 %0, %1, %2;" : "=r"(kp[i]) : "f"(acc[2 * i + 1]), "f"(acc[2 * i]));
          asm volatile("cvt.rn.bf16x2.f32 %0, %1, %2;" : "=r"(vp[i]) : "f"(acc[64 + 2 * i + 1]), "f"(acc[64 + 2 * i]));
        }
        zero_regs(accq);
#pragma unroll 1
        do step<128, true>(c, pp, accq); while (pp.g < J_Q + 1 + wg);
        const uint32_t phi_t = sb + SM_SCR + wg * 16384, v_t = phi_t + 8192;
        wait_empty(sb, 13);
        mbar_wait(sb + B_WPHI, 0);
        if (lane < 16) sts4(v_t + c.w4 * 2048 + lane * 128 + ((4 ^ (lane & 7)) << 4), 0x3f803f80u, 0x3f803f80u, 0x3f803f80u, 0x3f803f80u);
        float4* dst = &g_kvacc[epoch & 1][n * 4 * 640 + c.tid];
        uint32_t ph[16] = {};
        {
          float pk[4][16];
          wgmma_fence();
#pragma unroll
          for (int hh = 0; hh < 4; hh++) phi_mma(pk[hh], kp + hh * 8, sb + SM_WPHI + hh * 2048);
          wgmma_commit();
          wgmma_wait<0>();
          release_stage(c, pp.g - 1);
#pragma unroll
          for (int hh = 0; hh < 4; hh++) {
            fence_regs(pk[hh]);
#pragma unroll
            for (int i = 0; i < 8; i++) kp[hh * 8 + i] = pack_bf16(pk[hh][2 * i], pk[hh][2 * i + 1]);
          }
        }
#pragma unroll 1
        for (int hh = 0; ; hh++) {
          float kv[20];
          if (hh) {
            bar_sync(1 + wg, 128);
#pragma unroll
            for (int jj = 0; jj < 4; jj++) stmatrix_x4(stm_addr(c, phi_t + c.w4 * 2048, jj * 2), ph[4 * jj], ph[4 * jj + 1], ph[4 * jj + 2], ph[4 * jj + 3]);
#pragma unroll
            for (int jj = 0; jj < 2; jj++) stmatrix_x4(stm_addr(c, v_t + c.w4 * 2048, jj * 2), vp[4 * jj], vp[4 * jj + 1], vp[4 * jj + 2], vp[4 * jj + 3]);
            fence_async_smem();
#pragma unroll
            for (int i = 0; i < 24; i++) vp[i] = vp[i + 8];
            bar_sync(1 + wg, 128);
          }
          wgmma_fence();
          wgmma_ssz_n40<1, 1, H128>(kv, desc_lo(phi_t, 8192), desc_lo(v_t, 8192));
#pragma unroll
          for (int s = 1; s < 4; s++)
            wgmma_ss_n40<1, 1, H128>(kv, desc_lo(phi_t + s * 2048, 8192), desc_lo(v_t + s * 2048, 8192));
          wgmma_commit();
#pragma unroll
          for (int s = 0; s < 2; s++) {
            wait_full(c, pp);
            wgmma_fence();
            mma4<128, 0>(c, accq, pp);
            wgmma_commit();
            pp.g++; pp.a = next_slot<4, true>(pp.a, sb);
          }
          if (hh < 4) {
            float pk[16];
#pragma unroll
            for (int i = 0; i < 8; i++) { pk[2 * i] = bf_lo(kp[i]); pk[2 * i + 1] = bf_hi(kp[i]); }
            dual_softmax(pk, ph);
          }
          wgmma_wait<2>();
          fence_regs(kv);
          if (hh) {
#pragma unroll
            for (int j = 0; j < 5; j++) red_add4(dst + j * 128, kv[4 * j], kv[4 * j + 1], kv[4 * j + 2], kv[4 * j + 3]);
            dst += 640;
          }
          if (hh == 4) break;
#pragma unroll
          for (int i = 0; i < 24; i++) kp[i] = kp[i + 8];
          wgmma_wait<0>();
          release_stage(c, pp.g - 2); release_stage(c, pp.g - 1);
        }
        __syncwarp();
        if (lane == 0) mbar_arrive(sb + B_KV);
        wgmma_wait<1>();
        release_stage(c, pp.g - 2);
        if (tid == 0) TL(5);
#pragma unroll 1
        do step<128, true>(c, pp, accq); while (pp.g < J_WO);
      }
    }
    float accw[64];
    {
      wgmma_wait<0>();
      fence_regs(accq);
      release_stage(c, J_WO - 1);
      if (tid == 0) TL(6);
      uint32_t ph[4][16];
      {
        float pq[4][16];
        uint32_t qp[32];
#pragma unroll
        for (int i = 0; i < 32; i++) qp[i] = pack_bf16(accq[2 * i], accq[2 * i + 1]);
        wgmma_fence();
#pragma unroll
        for (int hh = 0; hh < 4; hh++) phi_mma(pq[hh], qp + hh * 8, sb + SM_WPHI + hh * 2048);
        wgmma_commit();
        wgmma_wait<0>();
#pragma unroll
        for (int hh = 0; hh < 4; hh++) fence_regs(pq[hh]);
#pragma unroll 1
        for (int j = 0; j < 2; j++) {
#pragma unroll
          for (int i = 0; i < 16; i++) { ph[0][i] = ph[2][i]; ph[1][i] = ph[3][i]; }
          dual_softmax(pq[0], ph[2]); dual_softmax(pq[1], ph[3]);
#pragma unroll
          for (int i = 0; i < 16; i++) { pq[0][i] = pq[2][i]; pq[1][i] = pq[3][i]; }
        }
      }
      if (tid == 0) TL(19);
      {
        uint32_t mask = 0;
        poll_flags(g_kvflag + n * 32, lane, epoch, 0xFFFFu, mask);
        if (tid == 0) TL(7);
        uint4 v[10];
        const float4* src = &g_kvacc[epoch & 1][(n * 4 + wg * 2) * 640 + c.tid];
#pragma unroll
        for (int i = 0; i < 10; i++) v[i] = ld_vol4(src + i * 128);
        int f = c.w4 * 16 + (lane >> 2);
#pragma unroll
        for (int i = 0; i < 10; i++) {
          uint32_t a = sb + SM_SCR + (wg * 2 + i / 5) * 8192 + f * 128 + (((i % 5) ^ (f & 7)) << 4) + q * 4;
          sts1(a, pack_bf16(__uint_as_float(v[i].x), __uint_as_float(v[i].y)));
          sts1(a + 1024, pack_bf16(__uint_as_float(v[i].z), __uint_as_float(v[i].w)));
        }
        fence_async_smem();
      }
      bar_sync(3, 256);
      float nd[4][20];
      wgmma_fence();
#pragma unroll
      for (int hh = 0; hh < 4; hh++) {
        const uint32_t db = desc_lo(sb + SM_SCR + hh * 8192, 8192);
        wgmma_rsz_n40<1, H128>(nd[hh], ph[hh][0], ph[hh][1], ph[hh][2], ph[hh][3], db);
#pragma unroll
        for (int s = 1; s < 4; s++) wgmma_rs_n40<1, H128>(nd[hh], ph[hh][4 * s], ph[hh][4 * s + 1], ph[hh][4 * s + 2], ph[hh][4 * s + 3], db + s * 128);
      }
      wgmma_commit();
      wait_empty(sb, NEED<J_WO + 3>);
      pp.a = sb + OFF<J_WO>;
      wgmma_wait<0>();
      if (c.tid < 2) mbar_arrive_cl(c.ebase + (B_SCR - B_EMPTY));
#pragma unroll
      for (int hh = 0; hh < 4; hh++) {
        fence_regs(nd[hh]);
        float i0 = rcp(nd[hh][16] + 1e-6f), i1 = rcp(nd[hh][18] + 1e-6f);
#pragma unroll
        for (int jj = 0; jj < 2; jj++)
          stmatrix_x4(stm_addr(c, sb + OFF<J_WO> + (hh & 2) * 32768 + wrow, (hh & 1) * 4 + jj * 2), pack_bf16(nd[hh][8 * jj] * i0, nd[hh][8 * jj + 1] * i0),
                      pack_bf16(nd[hh][8 * jj + 2] * i1, nd[hh][8 * jj + 3] * i1), pack_bf16(nd[hh][8 * jj + 4] * i0, nd[hh][8 * jj + 5] * i0), pack_bf16(nd[hh][8 * jj + 6] * i1, nd[hh][8 * jj + 7] * i1));
      }
      fence_async_smem();
      bar_sync(1 + wg, 128);
      if (c.tid < 2) mbar_arrive(sb + B_T0 + c.tid * 8);
      if (tid == 0) TL(8);
      zero_regs(accw);
      wait_full(c, pp);
      wgmma_fence(); mma4<128, 0>(c, accw, pp); wgmma_commit();
      pp.g++; pp.a += 32768;
    }
    float prev[96];
    float mr0, mr1;
    {
      uint32_t xr[32];
#pragma unroll
      for (int j = 0; j < 16; j++) {
        xr[2 * j] = ld_nc1(p.x + (size_t)r0 * DM + n * 128 + j * 8 + q * 2);
        xr[2 * j + 1] = ld_nc1(p.x + (size_t)(r0 + 8) * DM + n * 128 + j * 8 + q * 2);
      }
#pragma unroll 1
      do step<128, false>(c, pp, accw); while (pp.g < J_F1);
      mbar_wait(sb + B_VEC, 0);
      wait_empty(sb, NEED<J_F1 + 3>);
      wgmma_wait<0>();
      fence_regs(accw);
      release_stage(c, J_F1 - 1);
      if (tid == 0) TL(9);
#pragma unroll
      for (int pc = 0; pc < 2; pc++) {
#pragma unroll
        for (int jj = 0; jj < 4; jj++) {
          uint32_t r[4];
#pragma unroll
          for (int e = 0; e < 2; e++) {
            int j = pc * 8 + jj * 2 + e;
            uint2 gv = lds2(sb + SM_VEC + (j * 4 + q) * 16);
            float ga0 = bf_lo(gv.x), ga1 = bf_hi(gv.x);
            xr[2 * j] = pack_bf16(fmaf(ga0, accw[4 * j], bf_lo(xr[2 * j])), fmaf(ga1, accw[4 * j + 1], bf_hi(xr[2 * j])));
            xr[2 * j + 1] = pack_bf16(fmaf(ga0, accw[4 * j + 2], bf_lo(xr[2 * j + 1])), fmaf(ga1, accw[4 * j + 3], bf_hi(xr[2 * j + 1])));
            r[2 * e] = hmul2(xr[2 * j], gv.y); r[2 * e + 1] = hmul2(xr[2 * j + 1], gv.y);
          }
          stmatrix_x4(stm_addr(c, sb + (pc ? OFF<J_F1 + 2> : OFF<J_F1>) + wrow, jj * 2), r[0], r[1], r[2], r[3]);
        }
        fence_async_smem();
        bar_sync(1 + wg, 128);
        if (c.tid == 0) mbar_arrive(sb + B_T0 + pc * 8);
        if (pc == 0) {
          wait_full(c, pp);
          wgmma_fence(); mma4<192, 1>(c, prev, pp); wgmma_commit();
          pp.g++; pp.a += 40960;
        }
      }
      if (tid == 0) TL(10);
      wait_full(c, pp);
      wgmma_fence(); mma4<192, 0>(c, prev, pp); wgmma_commit();
      {
        float s0 = 0.f, s1 = 0.f, q0 = 0.f, q1 = 0.f;
#pragma unroll
        for (int j = 0; j < 16; j++) {
          float a0 = bf_lo(xr[2 * j]), a1 = bf_hi(xr[2 * j]), b0 = bf_lo(xr[2 * j + 1]), b1 = bf_hi(xr[2 * j + 1]);
          s0 += a0 + a1; s1 += b0 + b1; q0 = fmaf(a0, a0, fmaf(a1, a1, q0)); q1 = fmaf(b0, b0, fmaf(b1, b1, q1));
        }
        float ks = (q & 1) ? s1 : s0, kq = (q & 1) ? q1 : q0;
        ks += __shfl_xor_sync(~0u, (q & 1) ? s0 : s1, 1); kq += __shfl_xor_sync(~0u, (q & 1) ? q0 : q1, 1);
        ks += __shfl_xor_sync(~0u, ks, 2); kq += __shfl_xor_sync(~0u, kq, 2);
        if (q < 2) st_vol4(&g_st2pk[n * SEQ + r0 + 8 * q], __float_as_uint(ks), epoch, __float_as_uint(kq), epoch);
      }
#pragma unroll
      for (int i = 0; i < 8; i++) g_x1f[(b * 8 + i) * 256 + tid] = make_uint4(xr[4 * i], xr[4 * i + 1], xr[4 * i + 2], xr[4 * i + 3]);
      wgmma_wait<1>();
      release_stage(c, pp.g - 1);
      pp.g++; pp.a += 40960;
#pragma unroll 1
      do step<192, false>(c, pp, prev); while (pp.g < J_F1A);
    }
    float acc[64], accb[64];
    const uint32_t ut = sb + SM_GS1 + q * 16;
    auto first_step = [&](float (&a)[64]) {
      wait_full(c, pp);
      wgmma_fence(); mma4<128, 2>(c, a, pp, 0); wgmma_commit();
    };
    auto advance = [&]() {
      wgmma_wait<1>();
      release_stage(c, pp.g - 1);
      pp.g++; pp.a = next_slot<4, false>(pp.a, sb);
    };
    auto epi_steps = [&](auto nch, float (&a)[64], const float* pv, uint32_t utj, uint8_t* hid, uint32_t* flag) {
      constexpr int NCH = decltype(nch)::value;
#pragma unroll
      for (int s = 1; s < 2 * NCH + 2; s++) {
        wait_full(c, pp);
        wgmma_fence(); mma4<128, 0>(c, a, pp); wgmma_commit();
        if ((s & 1) && s < 2 * NCH) {
          const int ch = s >> 1;
          if (!(ch & 1)) stg_acquire(c);
#pragma unroll
          for (int jj = 0; jj < 2; jj++) {
            uint32_t r[4];
#pragma unroll
            for (int e = 0; e < 2; e++) {
              const int j = ch * 4 + jj * 2 + e;
              uint4 uv = lds4(utj + j * 64);
              float u0 = __uint_as_float(uv.x), t0 = __uint_as_float(uv.y), u1 = __uint_as_float(uv.z), t1 = __uint_as_float(uv.w);
              uint32_t z0 = pack_relu(fmaf(rs0, pv[4 * j], fmaf(mr0, u0, t0)), fmaf(rs0, pv[4 * j + 1], fmaf(mr0, u1, t1)));
              uint32_t z1 = pack_relu(fmaf(rs1, pv[4 * j + 2], fmaf(mr1, u0, t0)), fmaf(rs1, pv[4 * j + 3], fmaf(mr1, u1, t1)));
              r[2 * e] = hmul2(z0, z0); r[2 * e + 1] = hmul2(z1, z1);
            }
            stmatrix_x4(stm_addr(c, c.stg, (ch & 1) * 4 + jj * 2), r[0], r[1], r[2], r[3]);
          }
          if (ch & 1) stg_store(c, hid + (ch >> 1) * 16384);
        }
        advance();
      }
      warp_publish(c, flag);
      if (tid == 0) TL(54 + (pp.g >> 4) - 4);
    };
    zero_regs(acc);
    pp.a = sb + OFF<J_F1A>;
    first_step(acc);
    {
      uint4 a0, a1, b0, b1;
      poll4x2(&g_st2pk[q * 2 * SEQ + r0], &g_st2pk[(q * 2 + 1) * SEQ + r0], epoch, a0, a1);
      poll4x2(&g_st2pk[q * 2 * SEQ + r0 + 8], &g_st2pk[(q * 2 + 1) * SEQ + r0 + 8], epoch, b0, b1);
      float s0 = __uint_as_float(a0.x) + __uint_as_float(a1.x), s1 = __uint_as_float(b0.x) + __uint_as_float(b1.x);
      float q0 = __uint_as_float(a0.z) + __uint_as_float(a1.z), q1 = __uint_as_float(b0.z) + __uint_as_float(b1.z);
#pragma unroll
      for (int o = 1; o < 4; o <<= 1) {
        s0 += __shfl_xor_sync(~0u, s0, o); s1 += __shfl_xor_sync(~0u, s1, o); q0 += __shfl_xor_sync(~0u, q0, o); q1 += __shfl_xor_sync(~0u, q1, o);
      }
      s0 *= (1.f / DM); s1 *= (1.f / DM);
      rs0 = rsqrtf(fmaxf(fmaf(q0, 1.f / DM, -s0 * s0), 0.f) + 1e-5f); rs1 = rsqrtf(fmaxf(fmaf(q1, 1.f / DM, -s1 * s1), 0.f) + 1e-5f);
      mr0 = -s0 * rs0; mr1 = -s1 * rs1;
      mbar_wait(sb + B_UT, 0);
    }
    advance();
    fence_regs(prev);
    if (tid == 0) TL(11);
    epi_steps(std::integral_constant<int, 6>(), acc, prev, ut, act + (48 + 3 * n) * 16384 + wrow, wflag + 128);
#pragma unroll 1
    do step<128, false>(c, pp, acc); while (pp.g < J_F1A + 16);
    zero_regs(accb);
    first_step(accb);
    advance();
    fence_regs(acc);
    if (tid == 0) TL(13);
    epi_steps(std::integral_constant<int, 4>(), accb, acc, ut + 6 * 256, act + (72 + 2 * n) * 16384 + wrow, wflag + 192);
#pragma unroll 1
    do step<128, false>(c, pp, accb); while (pp.g < J_F1A + 32);
    first_step(acc);
    advance();
    fence_regs(accb);
    if (tid == 0) TL(15);
    epi_steps(std::integral_constant<int, 4>(), acc, accb, ut + 10 * 256, act + (88 + 2 * n) * 16384 + wrow, wflag + 256);
#pragma unroll 1
    do {
      step<128, false>(c, pp, acc);
    } while (pp.g < LAST_REL + 2);
    uint32_t xf[32];
#pragma unroll
    for (int i = 0; i < 8; i++) {
      uint4 v = ld_vol4(&g_x1f[(b * 8 + i) * 256 + tid]);
      xf[4 * i] = v.x; xf[4 * i + 1] = v.y; xf[4 * i + 2] = v.z; xf[4 * i + 3] = v.w;
    }
#pragma unroll 1
    do {
      wait_full(c, pp);
      wgmma_fence();
      mma4<128, 0>(c, acc, pp);
      wgmma_commit();
      pp.g++; pp.a = next_slot<4, false>(pp.a, sb);
    } while (pp.g < NST);
    wgmma_wait<0>();
    fence_regs(acc);
    if (tid == 0) TL(17);
#pragma unroll
    for (int pc = 0; pc < 2; pc++) {
      const uint32_t ob = sb + pc * 32768 + wrow;
#pragma unroll
      for (int jj = 0; jj < 4; jj++) {
        uint32_t r[4];
#pragma unroll
        for (int e = 0; e < 2; e++) {
          int j = pc * 8 + jj * 2 + e;
          uint2 gv = lds2(sb + SM_VEC + (j * 4 + q) * 16 + 8);
          float gb0 = bf_lo(gv.x), gb1 = bf_hi(gv.x), b20 = bf_lo(gv.y), b21 = bf_hi(gv.y);
          uint32_t x0 = xf[2 * j], x1 = xf[2 * j + 1];
          r[2 * e] = pack_bf16(fmaf(gb0, acc[4 * j] + b20, bf_lo(x0)), fmaf(gb1, acc[4 * j + 1] + b21, bf_hi(x0)));
          r[2 * e + 1] = pack_bf16(fmaf(gb0, acc[4 * j + 2] + b20, bf_lo(x1)), fmaf(gb1, acc[4 * j + 3] + b21, bf_hi(x1)));
        }
        stmatrix_x4(stm_addr(c, ob, jj * 2), r[0], r[1], r[2], r[3]);
      }
      fence_async_smem();
      __syncwarp();
      if (lane == 0) { tma_store_2d(&p.tm_out, ob, n * 128 + pc * 64, m * 128 + wg * 64 + c.w4 * 16); bulk_commit(); }
    }
    if (lane == 0) bulk_wait_read0();
    if (tid == 0) TL(18);
  }
}

typedef CUresult (*PFN_encodeTiled)(CUtensorMap*, CUtensorMapDataType, cuuint32_t, void*, const cuuint64_t*, const cuuint64_t*, const cuuint32_t*,
                                    const cuuint32_t*, CUtensorMapInterleave, CUtensorMapSwizzle, CUtensorMapL2promotion, CUtensorMapFloatOOBfill);
static void map_2d(PFN_encodeTiled enc, CUtensorMap* m, const void* ptr, uint64_t rows, uint64_t cols, uint32_t brows, uint32_t bcols, CUtensorMapSwizzle sw, uint64_t ld = 0) {
  cuuint64_t dims[2] = {cols, rows}; cuuint64_t strides[1] = {(ld ? ld : cols) * 2}; cuuint32_t box[2] = {bcols, brows}; cuuint32_t es[2] = {1, 1};
  enc(m, CU_TENSOR_MAP_DATA_TYPE_BFLOAT16, 2, (void*)ptr, dims, strides, box, es, CU_TENSOR_MAP_INTERLEAVE_NONE, sw,
      CU_TENSOR_MAP_L2_PROMOTION_L2_256B, CU_TENSOR_MAP_FLOAT_OOB_FILL_NONE);
}
static void map_3d(PFN_encodeTiled enc, CUtensorMap* m, const void* ptr, uint64_t d0, uint64_t d1, uint64_t d2, uint64_t s1, uint64_t s2,
                   uint32_t b0, uint32_t b1, uint32_t b2, CUtensorMapSwizzle sw) {
  cuuint64_t dims[3] = {d0, d1, d2}; cuuint64_t strides[2] = {s1, s2}; cuuint32_t box[3] = {b0, b1, b2}; cuuint32_t es[3] = {1, 1, 1};
  enc(m, CU_TENSOR_MAP_DATA_TYPE_BFLOAT16, 3, (void*)ptr, dims, strides, box, es, CU_TENSOR_MAP_INTERLEAVE_NONE, sw,
      CU_TENSOR_MAP_L2_PROMOTION_L2_256B, CU_TENSOR_MAP_FLOAT_OOB_FILL_NONE);
}
static void map_w(PFN_encodeTiled enc, CUtensorMap* m, const void* ptr, uint64_t rows, uint64_t ld, uint64_t col0, uint32_t nchunks, uint32_t parts) {
  cuuint64_t dims[4] = {64, rows, 8 * nchunks, parts}; cuuint64_t strides[3] = {ld * 2, 128, 8 * nchunks * 128};
  cuuint32_t box[4] = {64, 64, nchunks, parts}; cuuint32_t es[4] = {1, 1, 1, 1};
  enc(m, CU_TENSOR_MAP_DATA_TYPE_BFLOAT16, 4, (void*)((const bf16*)ptr + col0), dims, strides, box, es, CU_TENSOR_MAP_INTERLEAVE_NONE,
      CU_TENSOR_MAP_SWIZZLE_128B, CU_TENSOR_MAP_L2_PROMOTION_L2_256B, CU_TENSOR_MAP_FLOAT_OOB_FILL_NONE);
}

extern "C" void kernel_launch(void* const* d_in, const int* in_sizes, int n_in, void* d_out, int out_size) {
  void* fp = nullptr; cudaDriverEntryPointQueryResult qr;
  cudaGetDriverEntryPoint("cuTensorMapEncodeTiled", &fp, cudaEnableDefault, &qr);
  PFN_encodeTiled enc = (PFN_encodeTiled)fp;
  Params p;
  map_2d(enc, &p.tm_x, d_in[0], SEQ, DM, 64, 64, CU_TENSOR_MAP_SWIZZLE_128B);
  map_2d(enc, &p.tm_out, d_out, SEQ, DM, 16, 64, CU_TENSOR_MAP_SWIZZLE_128B);
  map_w(enc, &p.tm_b[0], d_in[1], DM, 3 * DM, DM, 2, 2);
  map_w(enc, &p.tm_b[1], d_in[1], DM, 3 * DM, 0, 2, 1);
  map_w(enc, &p.tm_b[2], d_in[3], DM, DM, 0, 2, 1);
  map_w(enc, &p.tm_b[3], d_in[5], DM, FF, 0, 3, 1);
  map_w(enc, &p.tm_b[4], d_in[5], DM, FF, 1536, 2, 1);
  map_w(enc, &p.tm_b[5], d_in[5], DM, FF, 2560, 2, 1);
  map_w(enc, &p.tm_b[6], d_in[7], FF, DM, 0, 2, 1);
  map_2d(enc, &p.tm_wphi, d_in[2], 1024, 32, 128, 32, CU_TENSOR_MAP_SWIZZLE_64B);
  map_2d(enc, &p.tm_g[0], (const bf16*)d_in[10] + 2048, DM, 4096, 64, 32, CU_TENSOR_MAP_SWIZZLE_64B, 6144);
  map_2d(enc, &p.tm_g[1], d_in[5], DM, FF, 64, 32, CU_TENSOR_MAP_SWIZZLE_64B);
  map_3d(enc, &p.tm_p[0], d_in[10], 2048, 256, 4, 12288, 256 * 12288, 16, 256, 4, CU_TENSOR_MAP_SWIZZLE_32B);
  map_3d(enc, &p.tm_p[1], d_in[0], 64, SEQ, 16, 2048, 128, 64, 16, 16, CU_TENSOR_MAP_SWIZZLE_128B);
  p.x = (const bf16*)d_in[0]; p.wqkv = (const bf16*)d_in[1]; p.wo = (const bf16*)d_in[3]; p.w1 = (const bf16*)d_in[5]; p.w2 = (const bf16*)d_in[7];
  p.b1 = (const bf16*)d_in[6]; p.b2 = (const bf16*)d_in[8]; p.c = (const bf16*)d_in[9]; p.wmod = (const bf16*)d_in[10];
  cudaFuncSetAttribute(mega_kernel, cudaFuncAttributeMaxDynamicSharedMemorySize, SM_TOTAL);
  mega_kernel<<<128, 384, SM_TOTAL>>>(p);
}
```
